```python
import torch

def _softmax(x, axis=-1):
    return torch.softmax(x, dim=axis)
def _gelu(x):
    return torch.nn.functional.gelu(x, approximate="tanh")
def _silu(x):
    return torch.nn.functional.silu(x)
def _sigmoid(x):
    return torch.sigmoid(x)
def _layernorm(x, axis=-1, eps=1e-5):
    m = x.mean(dim=axis, keepdim=True)
    v = x.var(dim=axis, keepdim=True, unbiased=False)
    return (x - m) / torch.sqrt(v + eps)
def _scatter_add(tgt, idx, src, axis=0):
    return tgt.clone().index_add_(axis, idx, src)
def _segment_sum(src, seg, n):
    out = torch.zeros((n,) + src.shape[1:], dtype=src.dtype)
    return out.index_add_(0, seg, src)
def _pad(x, pw):
    flat = tuple(v for pair in reversed(pw) for v in pair)
    return torch.nn.functional.pad(x, flat)

kernel_name = 'recurrent_scan__compressed_kv_cla__glu_gated_geglu__prompt'

def setup_inputs():

    _w = (lambda a: (lambda t: t.to(torch.bfloat16) if t.is_floating_point() else t)(torch.as_tensor(a)))
    def _A_setup():
        B, H, Sq, Sk, D, M = 1, 32, 2048, 2048, 128, 512
        Dc = 4 * D
        return {
            "x": _w((lambda *s: torch.randn(*s, dtype=torch.bfloat16) * 0.05)(B, Sq, M)),
            "c_kv": _w((lambda *s: torch.randn(*s, dtype=torch.bfloat16) * 1.6)(B, Sk, Dc)),
            "w_q": _w((lambda *s: torch.randn(*s, dtype=torch.bfloat16) * 1.6)(M, H, D) * (M ** -0.5)),
            "w_uk": _w((lambda *s: torch.randn(*s, dtype=torch.bfloat16) * 1.6)(Dc, H, D) * (Dc ** -0.5)),
            "w_uv": _w((lambda *s: torch.randn(*s, dtype=torch.bfloat16) * 1.6)(Dc, H, D) * (Dc ** -0.5)),
            "w_o": _w((lambda *s: torch.randn(*s, dtype=torch.bfloat16) * 1.6)(H, D, M) * ((H * D) ** -0.5)),
        }
    _A_in = _A_setup()

    def _B_setup():
        B, S, Dm, Df = 1, 2048, 512, 1792
        return {
            "x": _w((lambda *s: torch.randn(*s, dtype=torch.bfloat16) * 0.05)(B, S, Dm)),
            "w_gate": _w((lambda *s: torch.randn(*s, dtype=torch.bfloat16) * 0.2)(Dm, Df) * (Dm ** -0.5)),
            "w_up": _w((lambda *s: torch.randn(*s, dtype=torch.bfloat16) * 0.2)(Dm, Df) * (Dm ** -0.5)),
            "w_down": _w((lambda *s: torch.randn(*s, dtype=torch.bfloat16) * 0.2)(Df, Dm) * (Df ** -0.5)),
        }
    _B_in = _B_setup()

    return {
        "A_x": _A_in["x"],
        "A_c_kv": _A_in["c_kv"],
        "A_w_q": _A_in["w_q"],
        "A_w_uk": _A_in["w_uk"],
        "A_w_uv": _A_in["w_uv"],
        "A_w_o": _A_in["w_o"],
        "B_x": _B_in["x"],
        "B_w_gate": _B_in["w_gate"],
        "B_w_up": _B_in["w_up"],
        "B_w_down": _B_in["w_down"],
    }

def reference(A_x, A_c_kv, A_w_q, A_w_uk, A_w_uv, A_w_o, B_x, B_w_gate, B_w_up, B_w_down):
    def _A_ref(x, c_kv, w_q, w_uk, w_uv, w_o):
        B, Sq, M = x.shape[0], x.shape[1], x.shape[2]
        Sk = c_kv.shape[1]
        H, D = w_q.shape[1], w_q.shape[2]
        q = torch.einsum("bqm,mhd->bhqd", x, w_q)
        k = torch.einsum("bkc,chd->bhkd", c_kv, w_uk)
        v = torch.einsum("bkc,chd->bhkd", c_kv, w_uv)
        scores = torch.einsum("bhqd,bhkd->bhqk", q, k) * (D ** -0.5)
        off = Sk - Sq
        qi = torch.arange(Sq)[:, None]
        kj = torch.arange(Sk)[None, :]
        cmask = kj <= (qi + off)
        scores = torch.where(cmask[None, None], scores, -1e9)
        p = _softmax(scores, axis=-1)
        ctx = torch.einsum("bhqk,bhkd->bhqd", p, v)
        return torch.einsum("bhqd,hdm->bqm", ctx, w_o)

    def _B_ref(x, w_gate, w_up, w_down):
        g = torch.einsum("bsd,df->bsf", x, w_gate)
        u = torch.einsum("bsd,df->bsf", x, w_up)
        h = _gelu(g) * u
        return torch.einsum("bsf,fd->bsd", h, w_down)

    x = A_x
    xn = _layernorm(x, axis=-1)
    s = _A_ref(xn, A_c_kv, A_w_q, A_w_uk, A_w_uv, A_w_o)
    g = _silu(_B_ref(xn, B_w_gate, B_w_up, B_w_down))
    return x + s * g
```

```cpp
#include <cuda_runtime.h>
#include <cuda_bf16.h>
#include <cuda.h>
#include <stdint.h>
#include <string.h>
#include <stdio.h>

namespace {

constexpr int S_LEN = 2048, DM = 512, NH = 32, HD = 128, DFF = 1792;
constexpr int ACT_Q = 0, ACT_K = 4096, ACT_V = 8192, ACT_CTX = 12288, ACT_H = 16384, ACT_W = 16384 + DFF;
constexpr int NSLOT = 6, SLOT = 32768, STAGE2 = 49152;
constexpr int STG_OFF = NSLOT * SLOT;
constexpr int BAR_OFF = STG_OFF + 32768;
constexpr int SMEM_BYTES = BAR_OFF + 256 + 1024;
constexpr int MAXC = 66, P1LEN = 48, P2LEN = 32;
constexpr int PF1 = 2, PF2 = 16;
constexpr int NG2 = 16;
constexpr int FL_HEAD = 0, FL_H = 32, FL_CTX = 64, FL_DONE = 320, FL_TOTAL = 352;
constexpr uint32_t HEAD_CNT = 96, H_CNT = 112, CTX_CNT = 4;

struct Params {
  CUtensorMap act128, act64, wq, wuk, wuv, wg, wu, wo, wd, x128, ckv128, out64;
  uint8_t p1[MAXC][P1LEN];
  uint8_t p2[MAXC][P2LEN];
  uint8_t n2[MAXC];
  int nctas;
  uint32_t zero;
};

__device__ __nv_bfloat16 g_act[(size_t)S_LEN * ACT_W];
__device__ uint32_t g_flags[FL_TOTAL];

__device__ __forceinline__ uint32_t smem_u32(const void* p) { return (uint32_t)__cvta_generic_to_shared(p); }
__device__ __forceinline__ void mbar_init(uint32_t bar, uint32_t cnt) { asm volatile("mbarrier.init.shared::cta.b64 [%0], %1;" :: "r"(bar), "r"(cnt)); }
__device__ __forceinline__ void mbar_expect_tx(uint32_t bar, uint32_t bytes) { asm volatile("mbarrier.arrive.expect_tx.shared::cta.b64 _, [%0], %1;" :: "r"(bar), "r"(bytes) : "memory"); }
__device__ __forceinline__ void mbar_arrive(uint32_t bar) { asm volatile("mbarrier.arrive.shared::cta.b64 _, [%0];" :: "r"(bar) : "memory"); }
__device__ __forceinline__ void mbar_arrive_cluster(uint32_t remote_bar) { asm volatile("mbarrier.arrive.shared::cluster.b64 _, [%0];" :: "r"(remote_bar) : "memory"); }
__device__ __forceinline__ uint32_t mapa(uint32_t addr, uint32_t cta) { uint32_t r; asm("mapa.shared::cluster.u32 %0, %1, %2;" : "=r"(r) : "r"(addr), "r"(cta)); return r; }
__device__ __forceinline__ bool mbar_try(uint32_t bar, uint32_t parity) {
  uint32_t ok;
  asm volatile("{ .reg .pred p; mbarrier.try_wait.parity.shared::cta.b64 p, [%1], %2; selp.u32 %0, 1, 0, p; }" : "=r"(ok) : "r"(bar), "r"(parity) : "memory");
  return ok;
}
__device__ __forceinline__ void mbar_wait(uint32_t bar, uint32_t parity) {
  asm volatile("{ .reg .pred p;\n"
               "WAIT_%=: mbarrier.try_wait.parity.shared::cta.b64 p, [%0], %1;\n"
               "@!p bra WAIT_%=; }" :: "r"(bar), "r"(parity) : "memory");
}
__device__ __forceinline__ void tma_load(uint32_t dst, const CUtensorMap* m, int c0, int c1, uint32_t bar) {
  asm volatile("cp.async.bulk.tensor.2d.shared::cluster.global.mbarrier::complete_tx::bytes [%0], [%1, {%3, %4}], [%2];"
    :: "r"(dst), "l"(m), "r"(bar), "r"(c0), "r"(c1) : "memory");
}
__device__ __forceinline__ void tma_load_mc(uint32_t dst, const CUtensorMap* m, int c0, int c1, uint32_t bar) {
  asm volatile("cp.async.bulk.tensor.2d.shared::cluster.global.mbarrier::complete_tx::bytes.multicast::cluster [%0], [%1, {%3, %4}], [%2], %5;"
    :: "r"(dst), "l"(m), "r"(bar), "r"(c0), "r"(c1), "h"((uint16_t)3) : "memory");
}
__device__ __forceinline__ void tma_store(const CUtensorMap* m, uint32_t src, int c0, int c1) {
  asm volatile("cp.async.bulk.tensor.2d.global.shared::cta.bulk_group [%0, {%2, %3}], [%1];"
    :: "l"(m), "r"(src), "r"(c0), "r"(c1) : "memory");
}
__device__ __forceinline__ void bulk_commit() { asm volatile("cp.async.bulk.commit_group;" ::: "memory"); }
__device__ __forceinline__ void bulk_wait_read() { asm volatile("cp.async.bulk.wait_group.read 0;" ::: "memory"); }
__device__ __forceinline__ void bulk_wait_all() { asm volatile("cp.async.bulk.wait_group 0;" ::: "memory"); }
__device__ __forceinline__ void fence_async_smem() { asm volatile("fence.proxy.async.shared::cta;" ::: "memory"); }
__device__ __forceinline__ void fence_async_all() { asm volatile("fence.proxy.async;" ::: "memory"); }
__device__ __forceinline__ void cluster_arrive() { asm volatile("barrier.cluster.arrive.release.aligned;" ::: "memory"); }
__device__ __forceinline__ void cluster_wait() { asm volatile("barrier.cluster.wait.acquire.aligned;" ::: "memory"); }
__device__ __forceinline__ uint32_t cluster_rank() { uint32_t r; asm volatile("mov.u32 %0, %%cluster_ctarank;" : "=r"(r)); return r; }
__device__ __forceinline__ unsigned long long gtime() { unsigned long long t; asm volatile("mov.u64 %0, %%globaltimer;" : "=l"(t)); return t; }
__device__ __forceinline__ uint32_t clk() { uint32_t t; asm volatile("mov.u32 %0, %%clock;" : "=r"(t) :: "memory"); return t; }
__device__ __forceinline__ void tma_prefetch(const CUtensorMap* m, int c0, int c1) {
  asm volatile("cp.async.bulk.prefetch.tensor.2d.L2.global.tile [%0, {%1, %2}];" :: "l"(m), "r"(c0), "r"(c1) : "memory");
}
__device__ __forceinline__ void wg_fence() { asm volatile("wgmma.fence.sync.aligned;" ::: "memory"); }
__device__ __forceinline__ void wg_commit() { asm volatile("wgmma.commit_group.sync.aligned;" ::: "memory"); }
template <int N> __device__ __forceinline__ void wg_wait() { asm volatile("wgmma.wait_group.sync.aligned %0;" :: "n"(N) : "memory"); }
template <int N> __device__ __forceinline__ void pin(float (&d)[N]) {
#pragma unroll
  for (int i = 0; i < N; i++) asm volatile("" : "+f"(d[i]) :: "memory");
}
template <int N> __device__ __forceinline__ void pinu(uint32_t (&d)[N]) {
#pragma unroll
  for (int i = 0; i < N; i++) asm volatile("" : "+r"(d[i]));
}
template <int ID> __device__ __forceinline__ void bar_sync(int n) { asm volatile("bar.sync %0, %1;" :: "n"(ID), "r"(n) : "memory"); }
template <int ID> __device__ __forceinline__ void bar_arrive(int n) { asm volatile("bar.arrive %0, %1;" :: "n"(ID), "r"(n) : "memory"); }
__device__ __forceinline__ void ldsm4(uint32_t& r0, uint32_t& r1, uint32_t& r2, uint32_t& r3, uint32_t addr) {
  asm volatile("ldmatrix.sync.aligned.m8n8.x4.shared.b16 {%0, %1, %2, %3}, [%4];" : "=r"(r0), "=r"(r1), "=r"(r2), "=r"(r3) : "r"(addr) : "memory");
}
__device__ __forceinline__ void stsm4(uint32_t addr, uint32_t r0, uint32_t r1, uint32_t r2, uint32_t r3) {
  asm volatile("stmatrix.sync.aligned.m8n8.x4.shared.b16 [%0], {%1, %2, %3, %4};" :: "r"(addr), "r"(r0), "r"(r1), "r"(r2), "r"(r3) : "memory");
}
__device__ __forceinline__ uint32_t pack_bf16(float lo, float hi) {
  uint32_t r; asm("cvt.rn.bf16x2.f32 %0, %1, %2;" : "=r"(r) : "f"(hi), "f"(lo)); return r;
}
__device__ __forceinline__ uint32_t sub_bf16x2(uint32_t a, uint32_t b) { uint32_t r; asm("sub.rn.bf16x2 %0, %1, %2;" : "=r"(r) : "r"(a), "r"(b)); return r; }
__device__ __forceinline__ uint32_t add_bf16x2(uint32_t a, uint32_t b) { uint32_t r; asm("add.rn.bf16x2 %0, %1, %2;" : "=r"(r) : "r"(a), "r"(b)); return r; }
__device__ __forceinline__ uint32_t mul_bf16x2(uint32_t a, uint32_t b) { uint32_t r; asm("mul.rn.bf16x2 %0, %1, %2;" : "=r"(r) : "r"(a), "r"(b)); return r; }
__device__ __forceinline__ float bf_lo(uint32_t v) { return __uint_as_float(v << 16); }
__device__ __forceinline__ float bf_hi(uint32_t v) { return __uint_as_float(v & 0xFFFF0000u); }
__device__ __forceinline__ float ex2(float x) { float r; asm("ex2.approx.ftz.f32 %0, %1;" : "=f"(r) : "f"(x)); return r; }
__device__ __forceinline__ float rcp(float x) { float r; asm("rcp.approx.ftz.f32 %0, %1;" : "=f"(r) : "f"(x)); return r; }
__device__ __forceinline__ uint32_t ld_acquire(const uint32_t* p) { uint32_t v; asm volatile("ld.acquire.gpu.global.u32 %0, [%1];" : "=r"(v) : "l"(p) : "memory"); return v; }
__device__ __forceinline__ void red_release(uint32_t* p) { asm volatile("red.release.gpu.global.add.u32 [%0], 1;" :: "l"(p) : "memory"); }
__device__ __forceinline__ uint64_t mkdesc(uint32_t addr, uint32_t lbo, uint32_t sbo) {
  return (uint64_t)((addr & 0x3FFFF) >> 4) | ((uint64_t)(lbo >> 4) << 16) | ((uint64_t)(sbo >> 4) << 32) | (1ull << 62);
}

__device__ __forceinline__ void wgmma_rs_n128_kmaj(float (&d)[64], uint32_t a0, uint32_t a1, uint32_t a2, uint32_t a3, uint64_t db, int scale_d) {
  asm volatile("{ .reg .pred p; setp.ne.b32 p, %69, 0;\n"
      "wgmma.mma_async.sync.aligned.m64n128k16.f32.bf16.bf16 {"
      "%0, %1, %2, %3, %4, %5, %6, %7, %8, %9, %10, %11, %12, %13, %14, %15 "
      "%16, %17, %18, %19, %20, %21, %22, %23, %24, %25, %26, %27, %28, %29, %30, %31 "
      "%32, %33, %34, %35, %36, %37, %38, %39, %40, %41, %42, %43, %44, %45, %46, %47 "
      "%48, %49, %50, %51, %52, %53, %54, %55, %56, %57, %58, %59, %60, %61, %62, %63}, "
      "{%64, %65, %66, %67}, %68, p, 1, 1, 0; }\n"
    : "+f"(d[0]), "+f"(d[1]), "+f"(d[2]), "+f"(d[3]), "+f"(d[4]), "+f"(d[5]), "+f"(d[6]), "+f"(d[7]),
      "+f"(d[8]), "+f"(d[9]), "+f"(d[10]), "+f"(d[11]), "+f"(d[12]), "+f"(d[13]), "+f"(d[14]), "+f"(d[15]),
      "+f"(d[16]), "+f"(d[17]), "+f"(d[18]), "+f"(d[19]), "+f"(d[20]), "+f"(d[21]), "+f"(d[22]), "+f"(d[23]),
      "+f"(d[24]), "+f"(d[25]), "+f"(d[26]), "+f"(d[27]), "+f"(d[28]), "+f"(d[29]), "+f"(d[30]), "+f"(d[31]),
      "+f"(d[32]), "+f"(d[33]), "+f"(d[34]), "+f"(d[35]), "+f"(d[36]), "+f"(d[37]), "+f"(d[38]), "+f"(d[39]),
      "+f"(d[40]), "+f"(d[41]), "+f"(d[42]), "+f"(d[43]), "+f"(d[44]), "+f"(d[45]), "+f"(d[46]), "+f"(d[47]),
      "+f"(d[48]), "+f"(d[49]), "+f"(d[50]), "+f"(d[51]), "+f"(d[52]), "+f"(d[53]), "+f"(d[54]), "+f"(d[55]),
      "+f"(d[56]), "+f"(d[57]), "+f"(d[58]), "+f"(d[59]), "+f"(d[60]), "+f"(d[61]), "+f"(d[62]), "+f"(d[63])
    : "r"(a0), "r"(a1), "r"(a2), "r"(a3), "l"(db), "r"(scale_d));
}
__device__ __forceinline__ void wgmma_rs_n128_nmaj(float (&d)[64], uint32_t a0, uint32_t a1, uint32_t a2, uint32_t a3, uint64_t db, int scale_d) {
  asm volatile("{ .reg .pred p; setp.ne.b32 p, %69, 0;\n"
      "wgmma.mma_async.sync.aligned.m64n128k16.f32.bf16.bf16 {"
      "%0, %1, %2, %3, %4, %5, %6, %7, %8, %9, %10, %11, %12, %13, %14, %15 "
      "%16, %17, %18, %19, %20, %21, %22, %23, %24, %25, %26, %27, %28, %29, %30, %31 "
      "%32, %33, %34, %35, %36, %37, %38, %39, %40, %41, %42, %43, %44, %45, %46, %47 "
      "%48, %49, %50, %51, %52, %53, %54, %55, %56, %57, %58, %59, %60, %61, %62, %63}, "
      "{%64, %65, %66, %67}, %68, p, 1, 1, 1; }\n"
    : "+f"(d[0]), "+f"(d[1]), "+f"(d[2]), "+f"(d[3]), "+f"(d[4]), "+f"(d[5]), "+f"(d[6]), "+f"(d[7]),
      "+f"(d[8]), "+f"(d[9]), "+f"(d[10]), "+f"(d[11]), "+f"(d[12]), "+f"(d[13]), "+f"(d[14]), "+f"(d[15]),
      "+f"(d[16]), "+f"(d[17]), "+f"(d[18]), "+f"(d[19]), "+f"(d[20]), "+f"(d[21]), "+f"(d[22]), "+f"(d[23]),
      "+f"(d[24]), "+f"(d[25]), "+f"(d[26]), "+f"(d[27]), "+f"(d[28]), "+f"(d[29]), "+f"(d[30]), "+f"(d[31]),
      "+f"(d[32]), "+f"(d[33]), "+f"(d[34]), "+f"(d[35]), "+f"(d[36]), "+f"(d[37]), "+f"(d[38]), "+f"(d[39]),
      "+f"(d[40]), "+f"(d[41]), "+f"(d[42]), "+f"(d[43]), "+f"(d[44]), "+f"(d[45]), "+f"(d[46]), "+f"(d[47]),
      "+f"(d[48]), "+f"(d[49]), "+f"(d[50]), "+f"(d[51]), "+f"(d[52]), "+f"(d[53]), "+f"(d[54]), "+f"(d[55]),
      "+f"(d[56]), "+f"(d[57]), "+f"(d[58]), "+f"(d[59]), "+f"(d[60]), "+f"(d[61]), "+f"(d[62]), "+f"(d[63])
    : "r"(a0), "r"(a1), "r"(a2), "r"(a3), "l"(db), "r"(scale_d));
}
__device__ __forceinline__ void wgmma_ss_n256_nmaj(float (&d)[128], uint64_t da, uint64_t db, int scale_d) {
  asm volatile("{ .reg .pred p; setp.ne.b32 p, %130, 0;\n"
      "wgmma.mma_async.sync.aligned.m64n256k16.f32.bf16.bf16 {"
      "%0, %1, %2, %3, %4, %5, %6, %7, %8, %9, %10, %11, %12, %13, %14, %15 "
      "%16, %17, %18, %19, %20, %21, %22, %23, %24, %25, %26, %27, %28, %29, %30, %31 "
      "%32, %33, %34, %35, %36, %37, %38, %39, %40, %41, %42, %43, %44, %45, %46, %47 "
      "%48, %49, %50, %51, %52, %53, %54, %55, %56, %57, %58, %59, %60, %61, %62, %63 "
      "%64, %65, %66, %67, %68, %69, %70, %71, %72, %73, %74, %75, %76, %77, %78, %79 "
      "%80, %81, %82, %83, %84, %85, %86, %87, %88, %89, %90, %91, %92, %93, %94, %95 "
      "%96, %97, %98, %99, %100, %101, %102, %103, %104, %105, %106, %107, %108, %109, %110, %111 "
      "%112, %113, %114, %115, %116, %117, %118, %119, %120, %121, %122, %123, %124, %125, %126, %127}, "
      "%128, %129, p, 1, 1, 0, 1; }\n"
    : "+f"(d[0]), "+f"(d[1]), "+f"(d[2]), "+f"(d[3]), "+f"(d[4]), "+f"(d[5]), "+f"(d[6]), "+f"(d[7]),
      "+f"(d[8]), "+f"(d[9]), "+f"(d[10]), "+f"(d[11]), "+f"(d[12]), "+f"(d[13]), "+f"(d[14]), "+f"(d[15]),
      "+f"(d[16]), "+f"(d[17]), "+f"(d[18]), "+f"(d[19]), "+f"(d[20]), "+f"(d[21]), "+f"(d[22]), "+f"(d[23]),
      "+f"(d[24]), "+f"(d[25]), "+f"(d[26]), "+f"(d[27]), "+f"(d[28]), "+f"(d[29]), "+f"(d[30]), "+f"(d[31]),
      "+f"(d[32]), "+f"(d[33]), "+f"(d[34]), "+f"(d[35]), "+f"(d[36]), "+f"(d[37]), "+f"(d[38]), "+f"(d[39]),
      "+f"(d[40]), "+f"(d[41]), "+f"(d[42]), "+f"(d[43]), "+f"(d[44]), "+f"(d[45]), "+f"(d[46]), "+f"(d[47]),
      "+f"(d[48]), "+f"(d[49]), "+f"(d[50]), "+f"(d[51]), "+f"(d[52]), "+f"(d[53]), "+f"(d[54]), "+f"(d[55]),
      "+f"(d[56]), "+f"(d[57]), "+f"(d[58]), "+f"(d[59]), "+f"(d[60]), "+f"(d[61]), "+f"(d[62]), "+f"(d[63]),
      "+f"(d[64]), "+f"(d[65]), "+f"(d[66]), "+f"(d[67]), "+f"(d[68]), "+f"(d[69]), "+f"(d[70]), "+f"(d[71]),
      "+f"(d[72]), "+f"(d[73]), "+f"(d[74]), "+f"(d[75]), "+f"(d[76]), "+f"(d[77]), "+f"(d[78]), "+f"(d[79]),
      "+f"(d[80]), "+f"(d[81]), "+f"(d[82]), "+f"(d[83]), "+f"(d[84]), "+f"(d[85]), "+f"(d[86]), "+f"(d[87]),
      "+f"(d[88]), "+f"(d[89]), "+f"(d[90]), "+f"(d[91]), "+f"(d[92]), "+f"(d[93]), "+f"(d[94]), "+f"(d[95]),
      "+f"(d[96]), "+f"(d[97]), "+f"(d[98]), "+f"(d[99]), "+f"(d[100]), "+f"(d[101]), "+f"(d[102]), "+f"(d[103]),
      "+f"(d[104]), "+f"(d[105]), "+f"(d[106]), "+f"(d[107]), "+f"(d[108]), "+f"(d[109]), "+f"(d[110]), "+f"(d[111]),
      "+f"(d[112]), "+f"(d[113]), "+f"(d[114]), "+f"(d[115]), "+f"(d[116]), "+f"(d[117]), "+f"(d[118]), "+f"(d[119]),
      "+f"(d[120]), "+f"(d[121]), "+f"(d[122]), "+f"(d[123]), "+f"(d[124]), "+f"(d[125]), "+f"(d[126]), "+f"(d[127])
    : "l"(da), "l"(db), "r"(scale_d));
}

struct Cur {
  uint32_t s, p;
  __device__ __forceinline__ void next() { if (++s == NSLOT) { s = 0; p ^= 1; } }
};

struct Ctx {
  uint32_t base;
  uint32_t rel;
  uint32_t lane;
  __device__ __forceinline__ uint32_t full(uint32_t s) const { return base + BAR_OFF + s * 8; }
  __device__ __forceinline__ uint32_t empty(uint32_t s) const { return base + BAR_OFF + 64 + s * 8; }
  __device__ __forceinline__ uint32_t stg_full(uint32_t w) const { return base + BAR_OFF + 128 + w * 8; }
  __device__ __forceinline__ uint32_t stg_empty(uint32_t w) const { return base + BAR_OFF + 144 + w * 8; }
  __device__ __forceinline__ uint32_t done_bar() const { return base + BAR_OFF + 160; }
  __device__ __forceinline__ uint32_t full2(uint32_t s) const { return base + BAR_OFF + 176 + s * 8; }
  __device__ __forceinline__ uint32_t empty2(uint32_t s) const { return base + BAR_OFF + 208 + s * 8; }
  __device__ __forceinline__ uint32_t stage(uint32_t s) const { return base + s * STAGE2; }
  __device__ __forceinline__ void release2(uint32_t s) const { if (lane < 2) mbar_arrive_cluster(rel + (208 - 64) + s * 8); }
  __device__ __forceinline__ uint32_t slot(uint32_t s) const { return base + s * SLOT; }
  __device__ __forceinline__ void wait_full(const Cur& c) const { mbar_wait(full(c.s), c.p); }
  __device__ __forceinline__ void wait_stg(uint32_t w, uint32_t ph) const { mbar_wait(stg_empty(w), ph); }
  __device__ __forceinline__ void order_wait(uint32_t wg) const { if (wg) bar_sync<2>(256); else bar_sync<1>(256); }
  __device__ __forceinline__ void dump(int) const {}
  __device__ __forceinline__ void release(uint32_t s) const { if (lane < 2) mbar_arrive_cluster(rel + s * 8); }
  __device__ __forceinline__ void release_dep(uint32_t s, uint32_t dep) const { if (lane < 2) mbar_arrive_cluster(rel + s * 8 + dep); }
};

__device__ __forceinline__ void wait_flag(const uint32_t* f, uint32_t target) {
  while ((int32_t)(ld_acquire(f) - target) < 0) __nanosleep(64);
  fence_async_all();
}

#define TS(i)

__device__ __forceinline__ uint32_t first_stage(uint32_t ring_pos) { return ring_pos == 0 ? 0u : (ring_pos <= 3 ? 2u : 3u); }

__device__ __forceinline__ const CUtensorMap* slice_src(const Params& P, uint32_t op, uint32_t rank, int& col) {
  if (op < 96) { col = (op & 31) * 128 + rank * 64; return op < 32 ? &P.wuk : (op < 64 ? &P.wuv : &P.wq); }
  col = (op - 96) * 64;
  return rank ? &P.wu : &P.wg;
}
__device__ __forceinline__ void prefetch_w2(const Params& P, int s, int J, int col) {
  if ((s & 7) == J && s < 28 + 2 * NH) {
    const CUtensorMap* m = s < 28 ? &P.wd : &P.wo;
    const int k = (s < 28 ? s : s - 28) * 64;
    tma_prefetch(m, col, k);
    tma_prefetch(m, col + 64, k);
  }
}

__device__ __forceinline__ void producer(const Params& P, const Ctx& X, int cl, uint32_t rank) {
  Cur c{P.p1[cl][0] != 0xFF ? 4u : 0u, 0};
  auto acquire = [&]() { mbar_wait(X.empty(c.s), c.p ^ 1); mbar_expect_tx(X.full(c.s), SLOT); };
#pragma unroll 1
  for (int i = 1; i < P1LEN; i++) {
    const uint32_t op = P.p1[cl][i];
    if (op == 0xFF) break;
    if (op & 0x80) {
      const CUtensorMap* m = (op & 8) ? &P.x128 : &P.ckv128;
      const int row = (op & 7) * 256 + rank * 128;
      for (int k = 0; k < 4; k++) {
        acquire();
        tma_load(X.slot(c.s), m, k * 128, row, X.full(c.s));
        tma_load(X.slot(c.s) + 16384, m, k * 128 + 64, row, X.full(c.s));
        c.next();
      }
    } else {
      int col;
      const CUtensorMap* m = slice_src(P, op, rank, col);
      for (int k = 0; k < 4; k++) {
        acquire();
        tma_load_mc(X.slot(c.s) + rank * 16384, m, col, k * 128, X.full(c.s));
        c.next();
      }
    }
  }
  const uint32_t epoch1 = ld_acquire(&g_flags[FL_DONE]) / (uint32_t)P.nctas + 1;
  const uint32_t n2 = P.n2[cl];
  if (n2 != 0xFF) {
    int pv_col = 0;
    auto load_kv = [&](int col, int row) {
      acquire();
      tma_load_mc(X.slot(c.s) + rank * 16384, &P.act128, col + rank * 64, row, X.full(c.s));
      c.next();
    };
    for (uint32_t t = 0; t < n2; t++) {
      const uint32_t it = P.p2[cl][t];
      const int h = it >> 3, J = it & 7, n = 2 * J + 2;
      wait_flag(&g_flags[FL_HEAD + h], epoch1 * HEAD_CNT);
      acquire();
      {
        const int r_skip = J * 256 + (rank ? 64 : 0), r_full = J * 256 + (rank ? 128 : 192);
        const int col = ACT_Q + h * 128;
        tma_load(X.slot(c.s), &P.act64, col, r_skip, X.full(c.s));
        tma_load(X.slot(c.s) + 8192, &P.act64, col + 64, r_skip, X.full(c.s));
        tma_load(X.slot(c.s) + 16384, &P.act64, col, r_full, X.full(c.s));
        tma_load(X.slot(c.s) + 24576, &P.act64, col + 64, r_full, X.full(c.s));
        c.next();
      }
      load_kv(ACT_K + h * 128, (n - 1) * 128);
      if (t > 0) load_kv(pv_col, 0);
      for (int i = 1; i < n; i++) {
        load_kv(ACT_K + h * 128, (n - 1 - i) * 128);
        load_kv(ACT_V + h * 128, (n - i) * 128);
      }
      pv_col = ACT_V + h * 128;
    }
    if (n2 > 0) load_kv(pv_col, 0);
  } else {
    const uint32_t tile = P.p2[cl][0];
    const int J = tile >> 1, nh = tile & 1;
    const int row = J * 256 + rank * 128;
    uint32_t st = first_stage(c.s), ph = 0;
    wait_flag(&g_flags[FL_H + J], epoch1 * H_CNT);
    for (int s = 0; s < 28 + 2 * NH + 2; s++) {
      if (s < 4) {
        const uint32_t s0 = (st * 3) >> 1;
        mbar_wait(X.empty(s0), (s0 >= c.s ? c.p : c.p ^ 1) ^ 1);
        mbar_wait(X.empty(s0 + 1), (s0 + 1 >= c.s ? c.p : c.p ^ 1) ^ 1);
      } else {
        mbar_wait(X.empty2(st), ph ^ 1);
      }
      const uint32_t dst = X.stage(st), bar = X.full2(st);
      if (s < 28 + 2 * NH) {
        const bool dn = s < 28;
        const int ks = dn ? s : s - 28;
        mbar_expect_tx(bar, STAGE2);
        prefetch_w2(P, s + PF2, J, nh * 256 + rank * 128);
        const CUtensorMap* m = dn ? &P.wd : &P.wo;
        tma_load_mc(dst + 16384 + rank * 16384, m, nh * 256 + rank * 128, ks * 64, bar);
        tma_load_mc(dst + 16384 + rank * 16384 + 8192, m, nh * 256 + rank * 128 + 64, ks * 64, bar);
        if (!dn && !(ks & 1)) wait_flag(&g_flags[FL_CTX + (ks >> 1) * 8 + J], epoch1 * CTX_CNT);
        tma_load(dst, &P.act128, (dn ? ACT_H : ACT_CTX) + ks * 64, row, bar);
        if (s == 28 + 2 * NH - 16) for (int i = 0; i < 4; i++) tma_prefetch(&P.x128, nh * 256 + i * 64, row);
      } else {
        const int col = nh * 256 + (s - 28 - 2 * NH) * 128;
        mbar_expect_tx(bar, 32768);
        tma_load(dst, &P.x128, col, row, bar);
        tma_load(dst + 16384, &P.x128, col + 64, row, bar);
      }
      if ((s & 3) == 3) ph ^= 1;
      st = (st + 1) & 3;
    }
  }
}

__device__ __forceinline__ void storer(const Params& P, const Ctx& X, int cl, uint32_t rank, uint32_t w) {
  uint32_t ph = 0;
  const uint32_t stg = X.base + STG_OFF + w * 16384;
  auto put = [&](int col, int row, bool two, uint32_t* flag) {
    mbar_wait(X.stg_full(w), ph);
    tma_store(&P.act64, stg, col, row);
    if (two) tma_store(&P.act64, stg + 8192, col + 64, row);
    bulk_commit();
    bulk_wait_read();
    mbar_arrive(X.stg_empty(w));
    bulk_wait_all();
    red_release(flag);
    ph ^= 1;
  };
  const uint32_t pfp = P.p1[cl][0] & 7;
  int pair = 0;
#pragma unroll 1
  for (int i = 1 - PF1; i < P1LEN - PF1 - 1; i++) {
    const uint32_t nx = P.p1[cl][i + PF1 + 1];
    if (w == 0) {
      if (nx < 0x80 && ((i ^ (pfp >> 2)) & 1)) {
        int col;
        const CUtensorMap* m = slice_src(P, nx, rank, col);
        tma_prefetch(m, col, (pfp & 3) * 128);
      }
    } else if (nx == 0xFF && P.p1[cl][i + PF1] != 0xFF && P.n2[cl] == 0xFF) {
      const uint32_t tile = P.p2[cl][0];
      prefetch_w2(P, tile >> 1, tile >> 1, (tile & 1) * 256 + rank * 128);
      prefetch_w2(P, (tile >> 1) + 8, tile >> 1, (tile & 1) * 256 + rank * 128);
    }
    if (i < 0) continue;
    const uint32_t op = P.p1[cl][i];
    if (op == 0xFF) break;
    if (op & 0x80) { pair = op & 7; continue; }
    const int row = pair * 256 + rank * 128 + w * 64;
    if (op < 96) put((op < 32 ? ACT_K : (op < 64 ? ACT_V : ACT_Q)) + (op & 31) * 128, row, true, &g_flags[FL_HEAD + (op & 31)]);
    else put(ACT_H + (op - 96) * 64, row, false, &g_flags[FL_H + pair]);
  }
  const uint32_t n2 = P.n2[cl];
  if (n2 != 0xFF) {
    for (uint32_t t = 0; t < n2; t++) {
      const uint32_t it = P.p2[cl][t];
      const int h = it >> 3, J = it & 7;
      const bool skip = ((t ^ w) & 1);
      const int row = J * 256 + (skip ? (rank ? 64 : 0) : (rank ? 128 : 192));
      put(ACT_CTX + h * 128, row, true, &g_flags[FL_CTX + it]);
    }
  }
}

struct Cons {
  uint32_t wg;
  uint32_t frag;
  uint32_t xr;
  uint32_t chi;
  uint32_t stg_ph;
};

__device__ __forceinline__ void order_pass(uint32_t wg) { if (wg) bar_arrive<1>(256); else bar_arrive<2>(256); }

__device__ __forceinline__ void stg_publish(const Ctx& X, Cons& C) {
  fence_async_smem();
  __syncwarp();
  if (X.lane == 0) mbar_arrive(X.stg_full(C.wg));
  C.stg_ph ^= 1;
}

__device__ __forceinline__ float gelu_mul(float g, float u) {
  const float k0 = -2.0f * 0.7978845608028654f * 1.4426950408889634f;
  const float k1 = k0 * 0.044715f;
  const float e = ex2(g * fmaf(g * g, k1, k0));
  return g * rcp(1.0f + e) * u;
}

__device__ __forceinline__ void phase1(const Params& P, const Ctx& X, Cons& C, Cur& c, int cl) {
  uint32_t a[128];
  float acc[64];
  float rs0 = 1.0f, rs1 = 1.0f;
  bool need_var = false;
  const uint32_t stg = X.base + STG_OFF + C.wg * 16384;
  for (int i = 0; i < P1LEN; i++) {
    const uint32_t op = P.p1[cl][i];
    if (op == 0xFF) break;
    if (op & 0x80) {
      float s0 = 0.f, s1 = 0.f;
#pragma unroll
      for (int k = 0; k < 4; k++) {
        X.wait_full(c);
        if (i == 0 && k == 0 && C.wg == 0) TS(4);
        if (i == 0 && k == 3 && C.wg == 0) TS(5);
        const uint32_t b = X.slot(c.s) + C.wg * 8192 + C.frag;
#pragma unroll
        for (int kk = 0; kk < 8; kk++) {
          const uint32_t ch = ((kk & 3) * 2 + C.chi) ^ C.xr;
          ldsm4(a[(k * 8 + kk) * 4], a[(k * 8 + kk) * 4 + 1], a[(k * 8 + kk) * 4 + 2], a[(k * 8 + kk) * 4 + 3], b + (kk >> 2) * 16384 + ch * 16);
        }
        X.release_dep(c.s, (a[k * 32] ^ a[k * 32 + 4] ^ a[k * 32 + 8] ^ a[k * 32 + 12] ^ a[k * 32 + 16] ^ a[k * 32 + 20] ^ a[k * 32 + 24] ^ a[k * 32 + 28]) & P.zero);
        c.next();
        if (op & 8) {
#pragma unroll
          for (int r = k * 32; r < k * 32 + 32; r += 2) { s0 += bf_lo(a[r]) + bf_hi(a[r]); s1 += bf_lo(a[r + 1]) + bf_hi(a[r + 1]); }
        }
      }
      rs0 = 1.0f; rs1 = 1.0f;
      need_var = (op & 8) != 0;
      if (op & 8) {
        s0 += __shfl_xor_sync(0xffffffffu, s0, 1); s1 += __shfl_xor_sync(0xffffffffu, s1, 1);
        s0 += __shfl_xor_sync(0xffffffffu, s0, 2); s1 += __shfl_xor_sync(0xffffffffu, s1, 2);
        s0 *= 1.0f / DM; s1 *= 1.0f / DM;
        const uint32_t mb0 = pack_bf16(s0, s0), mb1 = pack_bf16(s1, s1);
        rs0 = s0 - bf_lo(mb0); rs1 = s1 - bf_lo(mb1);
#pragma unroll
        for (int r = 0; r < 128; r += 2) { a[r] = sub_bf16x2(a[r], mb0); a[r + 1] = sub_bf16x2(a[r + 1], mb1); }
      }
      continue;
    }
    if (i == 1 && C.wg == 0) TS(6);
    X.order_wait(C.wg);
    uint32_t prev = 0;
#pragma unroll
    for (int k = 0; k < 4; k++) {
      X.wait_full(c);
      const uint64_t db = mkdesc(X.slot(c.s), 16384, 1024);
      wg_fence();
#pragma unroll
      for (int kk = 0; kk < 8; kk++) {
        const int r = (k * 8 + kk) * 4;
        wgmma_rs_n128_nmaj(acc, a[r], a[r + 1], a[r + 2], a[r + 3], db + kk * 128, (k | kk) != 0);
      }
      wg_commit();
      if (k == 3) order_pass(C.wg);
      if (k > 0) { wg_wait<1>(); X.release(prev); }
      prev = c.s;
      c.next();
    }
    wg_wait<0>();
    pin(acc);
    X.release(prev);
    if (i == 1 && C.wg == 0) TS(7);
    if (need_var) {
      need_var = false;
      float v0 = 0.f, v1 = 0.f, w0 = 0.f, w1 = 0.f;
#pragma unroll
      for (int r = 0; r < 128; r += 2) {
        v0 = fmaf(bf_lo(a[r]), bf_lo(a[r]), v0); w0 = fmaf(bf_hi(a[r]), bf_hi(a[r]), w0);
        v1 = fmaf(bf_lo(a[r + 1]), bf_lo(a[r + 1]), v1); w1 = fmaf(bf_hi(a[r + 1]), bf_hi(a[r + 1]), w1);
      }
      v0 += w0; v1 += w1;
      v0 += __shfl_xor_sync(0xffffffffu, v0, 1); v1 += __shfl_xor_sync(0xffffffffu, v1, 1);
      v0 += __shfl_xor_sync(0xffffffffu, v0, 2); v1 += __shfl_xor_sync(0xffffffffu, v1, 2);
      rs0 = 1.0f / sqrtf(fmaxf(v0 * (1.0f / DM) - rs0 * rs0, 0.f) + 1e-5f);
      rs1 = 1.0f / sqrtf(fmaxf(v1 * (1.0f / DM) - rs1 * rs1, 0.f) + 1e-5f);
    }
#pragma unroll
    for (int j = 0; j < 16; j++) { acc[4 * j] *= rs0; acc[4 * j + 1] *= rs0; acc[4 * j + 2] *= rs1; acc[4 * j + 3] *= rs1; }
    X.wait_stg(C.wg, C.stg_ph ^ 1);
    if (op < 96) {
#pragma unroll
      for (int j = 0; j < 8; j++) {
        const uint32_t ch = ((j & 3) * 2 + C.chi) ^ C.xr;
        stsm4(stg + (j >> 2) * 8192 + C.frag + ch * 16, pack_bf16(acc[8 * j], acc[8 * j + 1]), pack_bf16(acc[8 * j + 2], acc[8 * j + 3]),
              pack_bf16(acc[8 * j + 4], acc[8 * j + 5]), pack_bf16(acc[8 * j + 6], acc[8 * j + 7]));
      }
    } else {
#pragma unroll
      for (int j = 0; j < 4; j++) {
        float hv[8];
#pragma unroll
        for (int e = 0; e < 8; e++) hv[e] = gelu_mul(acc[8 * j + e], acc[32 + 8 * j + e]);
        const uint32_t ch = (j * 2 + C.chi) ^ C.xr;
        stsm4(stg + C.frag + ch * 16, pack_bf16(hv[0], hv[1]), pack_bf16(hv[2], hv[3]), pack_bf16(hv[4], hv[5]), pack_bf16(hv[6], hv[7]));
      }
    }
    stg_publish(X, C);
  }
}

__device__ __forceinline__ void issue_qk(float (&s)[64], const uint32_t (&q)[32], uint32_t kslot) {
  const uint64_t db = mkdesc(kslot, 16, 1024);
  wg_fence();
#pragma unroll
  for (int kk = 0; kk < 8; kk++)
    wgmma_rs_n128_kmaj(s, q[4 * kk], q[4 * kk + 1], q[4 * kk + 2], q[4 * kk + 3], db + (kk >> 2) * 1024 + (kk & 3) * 2, kk != 0);
  wg_commit();
}
__device__ __forceinline__ void issue_pv(float (&o)[64], const uint32_t (&p)[32], uint32_t vslot, int accumulate) {
  const uint64_t db = mkdesc(vslot, 16384, 1024);
  wg_fence();
#pragma unroll
  for (int kk = 0; kk < 8; kk++)
    wgmma_rs_n128_nmaj(o, p[4 * kk], p[4 * kk + 1], p[4 * kk + 2], p[4 * kk + 3], db + kk * 128, kk ? 1 : accumulate);
  wg_commit();
}
__device__ __forceinline__ void row_max(const float (&s)[64], float& m0, float& m1) {
  float a0 = fmaxf(s[0], s[1]), a1 = fmaxf(s[2], s[3]), b0 = fmaxf(s[4], s[5]), b1 = fmaxf(s[6], s[7]);
#pragma unroll
  for (int j = 2; j < 16; j += 2) {
    a0 = fmaxf(a0, fmaxf(s[4 * j], s[4 * j + 1])); a1 = fmaxf(a1, fmaxf(s[4 * j + 2], s[4 * j + 3]));
    b0 = fmaxf(b0, fmaxf(s[4 * j + 4], s[4 * j + 5])); b1 = fmaxf(b1, fmaxf(s[4 * j + 6], s[4 * j + 7]));
  }
  m0 = fmaxf(a0, b0); m1 = fmaxf(a1, b1);
  m0 = fmaxf(m0, __shfl_xor_sync(0xffffffffu, m0, 1)); m1 = fmaxf(m1, __shfl_xor_sync(0xffffffffu, m1, 1));
  m0 = fmaxf(m0, __shfl_xor_sync(0xffffffffu, m0, 2)); m1 = fmaxf(m1, __shfl_xor_sync(0xffffffffu, m1, 2));
}
constexpr float P_LIMIT = 16777216.0f;
constexpr int PRE = 16;
constexpr float SM_SCALE = 0.08838834764831845f * 1.4426950408889634f;
__device__ __forceinline__ void exp_sum(float (&s)[64], float m0, float m1, float& l0, float& l1) {
  const float n0 = -m0 * SM_SCALE, n1 = -m1 * SM_SCALE;
  float a0 = 0.f, a1 = 0.f, b0 = 0.f, b1 = 0.f;
#pragma unroll
  for (int j = 0; j < 16; j++) {
    s[4 * j] = ex2(fmaf(s[4 * j], SM_SCALE, n0)); s[4 * j + 1] = ex2(fmaf(s[4 * j + 1], SM_SCALE, n0));
    s[4 * j + 2] = ex2(fmaf(s[4 * j + 2], SM_SCALE, n1)); s[4 * j + 3] = ex2(fmaf(s[4 * j + 3], SM_SCALE, n1));
    a0 += s[4 * j]; b0 += s[4 * j + 1]; a1 += s[4 * j + 2]; b1 += s[4 * j + 3];
  }
  l0 += a0 + b0; l1 += a1 + b1;
}
__device__ __forceinline__ void pack_p(const float (&s)[64], uint32_t (&p)[32]) {
#pragma unroll
  for (int i = 0; i < 32; i++) p[i] = pack_bf16(s[2 * i], s[2 * i + 1]);
}
__device__ __forceinline__ void attn_epilogue(const Ctx& X, Cons& C, const float (&o)[64], float l0, float l1) {
  l0 += __shfl_xor_sync(0xffffffffu, l0, 1); l1 += __shfl_xor_sync(0xffffffffu, l1, 1);
  l0 += __shfl_xor_sync(0xffffffffu, l0, 2); l1 += __shfl_xor_sync(0xffffffffu, l1, 2);
  const float i0 = 1.0f / l0, i1 = 1.0f / l1;
  const uint32_t stg = X.base + STG_OFF + C.wg * 16384;
  X.wait_stg(C.wg, C.stg_ph ^ 1);
#pragma unroll
  for (int j = 0; j < 8; j++) {
    const uint32_t ch = ((j & 3) * 2 + C.chi) ^ C.xr;
    stsm4(stg + (j >> 2) * 8192 + C.frag + ch * 16, pack_bf16(o[8 * j] * i0, o[8 * j + 1] * i0), pack_bf16(o[8 * j + 2] * i1, o[8 * j + 3] * i1),
          pack_bf16(o[8 * j + 4] * i0, o[8 * j + 5] * i0), pack_bf16(o[8 * j + 6] * i1, o[8 * j + 7] * i1));
  }
  stg_publish(X, C);
}

__device__ __forceinline__ void attention(const Params& P, const Ctx& X, Cons& C, Cur& c, int cl, uint32_t rank, uint32_t n2) {
  float s[64], o[64];
  uint32_t q[32], p[32];
  float m0 = 0.f, m1 = 0.f, l0 = 0.f, l1 = 0.f;
  int acc_o = 0;
  const int wrow = ((threadIdx.x >> 5) & 3) * 16 + (X.lane >> 2);
  const int tcol = (X.lane & 3) * 2;
#pragma unroll
  for (int i = 0; i < 64; i++) o[i] = 0.f;
#pragma unroll
  for (int i = 0; i < 32; i++) p[i] = 0u;
#define PT(i)
#define PM(i)
  for (uint32_t t = 0; t < n2; t++) {
    const uint32_t it = P.p2[cl][t];
    const int J = it & 7;
    const bool skip = ((t ^ C.wg) & 1);
    const int nblk = 2 * J + 2 - (skip ? 1 : 0);
    X.wait_full(c);
    {
      const uint32_t b = X.slot(c.s) + (skip ? 0 : 16384) + C.frag;
#pragma unroll
      for (int kk = 0; kk < 8; kk++) {
        const uint32_t ch = ((kk & 3) * 2 + C.chi) ^ C.xr;
        ldsm4(q[4 * kk], q[4 * kk + 1], q[4 * kk + 2], q[4 * kk + 3], b + (kk >> 2) * 8192 + ch * 16);
      }
      X.release_dep(c.s, (q[0] ^ q[4] ^ q[8] ^ q[12] ^ q[16] ^ q[20] ^ q[24] ^ q[28]) & P.zero);
      c.next();
    }
    Cur ck = c, cv = c, cs = c;
    if (skip) {
      X.wait_full(c); X.release(c.s); c.next();
      if (t > 0) { cv = c; c.next(); }
      ck = c; c.next();
      cs = c; c.next();
    } else {
      ck = c; c.next();
      if (t > 0) { cv = c; c.next(); }
    }
    X.wait_full(ck);
    if (t > 0) X.wait_full(cv);
    X.order_wait(C.wg);
    issue_qk(s, q, X.slot(ck.s));
    if (t > 0) issue_pv(o, p, X.slot(cv.s), acc_o); else wg_commit();
    order_pass(C.wg);
    wg_wait<1>();
    pin(s);
    X.release(ck.s);
    {
      const int lim = ((rank != 0) == skip ? 64 : 0) + wrow - tcol;
#pragma unroll
      for (int j = 0; j < 16; j++) {
        if (8 * j > lim) s[4 * j] = -INFINITY;
        if (8 * j + 1 > lim) s[4 * j + 1] = -INFINITY;
        if (8 * j > lim + 8) s[4 * j + 2] = -INFINITY;
        if (8 * j + 1 > lim + 8) s[4 * j + 3] = -INFINITY;
      }
    }
    const float pl0 = l0, pl1 = l1;
    row_max(s, m0, m1);
    l0 = 0.f; l1 = 0.f;
    exp_sum(s, m0, m1, l0, l1);
    wg_wait<0>();
    pin(o);
    if (t > 0) { X.release(cv.s); attn_epilogue(X, C, o, pl0, pl1); }
    if (skip) { X.wait_full(cs); X.release(cs.s); }
    pack_p(s, p);
    acc_o = 0;
    PM(7);
    for (int b = 1; b < nblk; b++) {
      ck = c; c.next();
      cv = c; c.next();
      X.wait_full(ck);
      X.wait_full(cv);
      X.order_wait(C.wg);
      PT(0);
      issue_qk(s, q, X.slot(ck.s));
      issue_pv(o, p, X.slot(cv.s), acc_o);
      order_pass(C.wg);
      PT(1);
      wg_wait<1>();
      pin(s);
      PT(2);
      X.release(ck.s);
      float a0, a1;
      {
        float e[PRE];
        const float z0 = -m0 * SM_SCALE, z1 = -m1 * SM_SCALE;
#pragma unroll
        for (int i = 0; i < PRE; i++) e[i] = ex2(fmaf(s[i], SM_SCALE, (i & 2) ? z1 : z0));
        PT(3);
        wg_wait<0>();
        pin(o);
        PT(4);
        X.release(cv.s);
        float b0 = 0.f, b1 = 0.f;
        a0 = 0.f; a1 = 0.f;
#pragma unroll
        for (int j = 0; j < 16; j++) {
          float e0, e1, e2, e3;
          if (4 * j < PRE) { e0 = e[(4 * j) % PRE]; e1 = e[(4 * j + 1) % PRE]; e2 = e[(4 * j + 2) % PRE]; e3 = e[(4 * j + 3) % PRE]; }
          else {
            e0 = ex2(fmaf(s[4 * j], SM_SCALE, z0)); e1 = ex2(fmaf(s[4 * j + 1], SM_SCALE, z0));
            e2 = ex2(fmaf(s[4 * j + 2], SM_SCALE, z1)); e3 = ex2(fmaf(s[4 * j + 3], SM_SCALE, z1));
          }
          a0 += e0; b0 += e1; a1 += e2; b1 += e3;
          p[2 * j] = pack_bf16(e0, e1); p[2 * j + 1] = pack_bf16(e2, e3);
        }
        a0 += b0; a1 += b1;
      }
      if (__any_sync(0xffffffffu, !(a0 + a1 <= P_LIMIT))) {
        float n0, n1;
        row_max(s, n0, n1);
        n0 = fmaxf(n0, m0); n1 = fmaxf(n1, m1);
        const float f0 = ex2((m0 - n0) * SM_SCALE), f1 = ex2((m1 - n1) * SM_SCALE);
        m0 = n0; m1 = n1;
        l0 *= f0; l1 *= f1;
        a0 = 0.f; a1 = 0.f;
        exp_sum(s, m0, m1, a0, a1);
#pragma unroll
        for (int j = 0; j < 16; j++) { o[4 * j] *= f0; o[4 * j + 1] *= f0; o[4 * j + 2] *= f1; o[4 * j + 3] *= f1; }
        pack_p(s, p);
      }
      l0 += a0; l1 += a1;
      PT(5);
      acc_o = 1;
    }
    PM(6);
  }
  if (n2 > 0) {
    X.wait_full(c);
    issue_pv(o, p, X.slot(c.s), acc_o);
    wg_wait<0>();
    pin(o);
    X.release(c.s);
    c.next();
    attn_epilogue(X, C, o, l0, l1);
  }
}

__device__ __forceinline__ void gemm2_loop(const Ctx& X, const Cons& C, uint32_t& st, uint32_t& n, float (&acc)[128], int nsteps) {
  uint32_t prev = 0;
  for (int s = 0; s < nsteps; s++) {
    mbar_wait(X.full2(st), (n >> 2) & 1);
    const uint64_t da = mkdesc(X.stage(st) + C.wg * 8192, 16, 1024);
    const uint64_t db = mkdesc(X.stage(st) + 16384, 8192, 1024);
    wg_fence();
#pragma unroll
    for (int kk = 0; kk < 4; kk++) wgmma_ss_n256_nmaj(acc, da + kk * 2, db + kk * 128, kk ? 1 : s);
    wg_commit();
    wg_wait<1>();
    if (s > 0) X.release2(prev);
    prev = st;
    st = (st + 1) & 3;
    n++;
  }
  wg_wait<0>();
  pin(acc);
  X.release2(prev);
}

__device__ __forceinline__ void gemm2(const Params& P, const Ctx& X, Cons& C, Cur& c, int cl, uint32_t rank) {
  float acc[128];
  uint32_t g[64];
  uint32_t st = first_stage(c.s), n = 0;
  gemm2_loop(X, C, st, n, acc, 28);
#pragma unroll
  for (int i = 0; i < 64; i++) {
    const uint32_t d = pack_bf16(acc[2 * i], acc[2 * i + 1]);
    const float d0 = bf_lo(d), d1 = bf_hi(d);
    g[i] = pack_bf16(d0 * rcp(1.0f + ex2(-1.4426950408889634f * d0)), d1 * rcp(1.0f + ex2(-1.4426950408889634f * d1)));
  }
#pragma unroll
  for (int i = 0; i < 128; i++) acc[i] = 0.f;
  TS(4 + C.wg);
  gemm2_loop(X, C, st, n, acc, 2 * NH);
  TS(6 + C.wg);
  const uint32_t tile = P.p2[cl][0];
  const int row = (tile >> 1) * 256 + rank * 128 + C.wg * 64, col = (tile & 1) * 256;
#pragma unroll
  for (int hf = 0; hf < 2; hf++) {
    mbar_wait(X.full2(st), (n >> 2) & 1);
    const uint32_t sl = X.stage(st) + C.wg * 8192;
#pragma unroll
    for (int j = 0; j < 8; j++) {
      const uint32_t ch = ((j & 3) * 2 + C.chi) ^ C.xr;
      const uint32_t addr = sl + (j >> 2) * 16384 + C.frag + ch * 16;
      uint32_t x[4];
      ldsm4(x[0], x[1], x[2], x[3], addr);
#pragma unroll
      for (int e = 0; e < 4; e++) {
        const int r = (hf * 8 + j) * 4 + e;
        x[e] = add_bf16x2(x[e], mul_bf16x2(pack_bf16(acc[2 * r], acc[2 * r + 1]), g[r]));
      }
      stsm4(addr, x[0], x[1], x[2], x[3]);
    }
    fence_async_smem();
    if (C.wg) bar_sync<4>(128); else bar_sync<3>(128);
    if ((threadIdx.x & 127) == 0) {
      tma_store(&P.out64, sl, col + hf * 128, row);
      tma_store(&P.out64, sl + 16384, col + hf * 128 + 64, row);
      bulk_commit();
    }
    st = (st + 1) & 3;
    n++;
  }
  if ((threadIdx.x & 127) == 0) bulk_wait_read();
  __syncwarp();
}

__global__ void __cluster_dims__(2, 1, 1) __launch_bounds__(384, 1) fused_kernel(const __grid_constant__ Params P) {
  extern __shared__ uint8_t smem_raw[];
  Ctx X;
  X.base = (smem_u32(smem_raw) + 1023) & ~1023u;
  X.lane = threadIdx.x & 31;
  X.rel = mapa(X.base + BAR_OFF + 64, X.lane & 1);
  const uint32_t rank = cluster_rank();
  const int cl = blockIdx.x >> 1;
  const uint32_t warp = __shfl_sync(0xffffffffu, threadIdx.x >> 5, 0);
  TS(0);
  if (warp == 9 && X.lane < 12) asm volatile("prefetch.tensormap [%0];" :: "l"(&P.act128 + X.lane) : "memory");
  if (threadIdx.x == 320) {
    const uint32_t op = P.p1[cl][1];
    if (op < 0x80) {
      int col;
      const CUtensorMap* m = slice_src(P, op, rank, col);
      tma_prefetch(m, col, (P.p1[cl][0] & 3) * 128);
    }
  }
  if (threadIdx.x == 256) {
    for (int i = 0; i < NSLOT; i++) { mbar_init(X.full(i), 1); mbar_init(X.empty(i), 16); }
    for (int i = 0; i < 2; i++) { mbar_init(X.stg_full(i), 4); mbar_init(X.stg_empty(i), 1); }
    for (int i = 0; i < 4; i++) { mbar_init(X.full2(i), 1); mbar_init(X.empty2(i), 16); }
    mbar_init(X.done_bar(), 11);
    asm volatile("fence.mbarrier_init.release.cluster;" ::: "memory");
    fence_async_all();
  }
  __syncthreads();
  asm volatile("barrier.cluster.arrive.relaxed.aligned;" ::: "memory");
  if (threadIdx.x == 256) {
    const uint32_t op = P.p1[cl][0];
    if (op != 0xFF) {
      const CUtensorMap* m = (op & 8) ? &P.x128 : &P.ckv128;
      const int row = (op & 7) * 256 + rank * 128;
      for (int k = 0; k < 4; k++) {
        mbar_expect_tx(X.full(k), SLOT);
        tma_load(X.slot(k), m, k * 128, row, X.full(k));
        tma_load(X.slot(k) + 16384, m, k * 128 + 64, row, X.full(k));
      }
    }
  }
  __syncwarp();
  cluster_wait();
  if (threadIdx.x == 0) TS(1);
  if (warp >= 8) {
    asm volatile("setmaxnreg.dec.sync.aligned.u32 24;");
    if (warp == 8) {
      if (X.lane == 0) {
        producer(P, X, cl, rank);
        mbar_arrive(X.done_bar());
      }
    } else if (warp < 11) {
      if (X.lane == 0) { storer(P, X, cl, rank, warp - 9); mbar_arrive(X.done_bar()); }
    } else {
      if (X.lane == 0) {
        const unsigned long long t0 = gtime();
        while (!mbar_try(X.done_bar(), 0)) {
          if (gtime() - t0 > 4000000000ull) __trap();
        }
        asm volatile("red.relaxed.gpu.global.add.u32 [%0], 1;" :: "l"(&g_flags[FL_DONE]) : "memory");
      }
    }
    __syncwarp();
    cluster_arrive();
    cluster_wait();
  } else {
    asm volatile("setmaxnreg.inc.sync.aligned.u32 240;");
    Cons C;
    C.wg = warp >> 2;
    {
      const uint32_t r = (warp & 3) * 16 + (X.lane & 7) + ((X.lane >> 3) & 1) * 8;
      C.frag = r * 128;
      C.xr = r & 7;
      C.chi = X.lane >> 4;
    }
    C.stg_ph = 0;
    Cur c{0, 0};
    if (C.wg == 1) bar_arrive<1>(256);
    phase1(P, X, C, c, cl);
    TS(2 + C.wg);
    X.dump(0);
    const uint32_t n2 = P.n2[cl];
    if (n2 != 0xFF) attention(P, X, C, c, cl, rank, n2);
    else gemm2(P, X, C, c, cl, rank);
    TS(8 + C.wg);
    X.dump(3);
    if (X.lane == 0) mbar_arrive(X.done_bar());
    __syncwarp();
    cluster_arrive();
    cluster_wait();
  }
}

typedef CUresult (*EncodeFn)(CUtensorMap*, CUtensorMapDataType, cuuint32_t, void*, const cuuint64_t*, const cuuint64_t*,
                             const cuuint32_t*, const cuuint32_t*, CUtensorMapInterleave, CUtensorMapSwizzle,
                             CUtensorMapL2promotion, CUtensorMapFloatOOBfill);

void make_map(EncodeFn enc, CUtensorMap* m, const void* ptr, uint64_t rows, uint64_t cols, uint32_t box_rows) {
  cuuint64_t dims[2] = {cols, rows};
  cuuint64_t strides[1] = {cols * 2};
  cuuint32_t box[2] = {64, box_rows};
  cuuint32_t es[2] = {1, 1};
  CUresult r = enc(m, CU_TENSOR_MAP_DATA_TYPE_BFLOAT16, 2, const_cast<void*>(ptr), dims, strides, box, es,
                   CU_TENSOR_MAP_INTERLEAVE_NONE, CU_TENSOR_MAP_SWIZZLE_128B, CU_TENSOR_MAP_L2_PROMOTION_L2_256B,
                   CU_TENSOR_MAP_FLOAT_OOB_FILL_NONE);
  if (r != CUDA_SUCCESS) fprintf(stderr, "tensor map encode failed: %d\n", (int)r);
}

void build_schedule(Params& P, int nc) {
  memset(P.p1, 0xFF, sizeof(P.p1));
  memset(P.p2, 0, sizeof(P.p2));
  memset(P.n2, 0, sizeof(P.n2));
  struct Seg { int cl, col, cnt; float t0; int pos; };
  static Seg segs[512];
  int nseg = 0;
  float tend[MAXC];
  int len[MAXC];
  for (int c = 0; c < nc; c++) { tend[c] = 0.f; len[c] = 0; }
  auto add_seg = [&](int c, int col, int cnt) {
    tend[c] += (col & 8) ? 0.9f : 0.5f;
    P.p1[c][len[c]++] = (uint8_t)(0x80 | col);
    segs[nseg++] = Seg{c, col, cnt, tend[c], len[c]};
    len[c] += cnt;
    tend[c] += cnt;
  };
  if (nc == 66) {
    for (int c = 0; c < 64; c++) add_seg(c, (c >= 32 ? 8 : 0) | (c & 7), 15);
    for (int p = 0; p < 8; p++) add_seg(64 + (p >> 2), p, 4);
  } else {
    const int per = (992 + nc - 1) / nc;
    int c = 0, left = per;
    for (int col = 0; col < 16; col++) {
      int need = (col & 8) ? 60 : 64;
      while (need > 0) {
        if (left == 0) { c++; left = per; }
        const int k = need < left ? need : left;
        add_seg(c, col, k);
        need -= k; left -= k;
      }
    }
  }
  for (int col = 0; col < 16; col++) {
    const int n = (col & 8) ? 60 : 64;
    int used[512];
    for (int i = 0; i < nseg; i++) used[i] = 0;
    for (int k = 0; k < n; k++) {
      int best = -1; float bt = 1e30f;
      for (int i = 0; i < nseg; i++) {
        if (segs[i].col != col || used[i] >= segs[i].cnt) continue;
        const float t = segs[i].t0 + used[i] + ((nc == 66 && segs[i].cl >= 64) ? 1000.f : 0.f);
        if (t < bt) { bt = t; best = i; }
      }
      const int op = (col & 8) ? (k < 28 ? 96 + k : 64 + (k - 28)) : ((k & 1) * 32 + (k >> 1));
      P.p1[segs[best].cl][segs[best].pos + used[best]] = (uint8_t)op;
      used[best]++;
    }
  }
  const int na = nc - NG2;
  for (int i = 0; i < NG2; i++) { P.n2[na + i] = 0xFF; P.p2[na + i][0] = (uint8_t)i; }
  int order[256]; float key[256];
  const float dh = 68.0f / na;
  for (int i = 0; i < 256; i++) { order[i] = i; key[i] = (i >> 3) * dh - (2 * (i & 7) + 1.5f); }
  for (int i = 1; i < 256; i++) {
    const int v = order[i]; int j = i - 1;
    while (j >= 0 && key[order[j]] > key[v]) { order[j + 1] = order[j]; j--; }
    order[j + 1] = v;
  }
  float av[MAXC];
  for (int c = 0; c < na; c++) av[c] = tend[c] * 2.0f * 0.9f;
  for (int i = 0; i < 256; i++) {
    int best = -1;
    for (int c = 0; c < na; c++) if (P.n2[c] < P2LEN && (best < 0 || av[c] < av[best])) best = c;
    P.p2[best][P.n2[best]++] = (uint8_t)order[i];
    av[best] += 2 * (order[i] & 7) + 1.5f + 0.2f;
  }
  P.nctas = 2 * nc;
  P.zero = 0;
}

}

extern "C" void kernel_launch(void* const* d_in, const int* in_sizes, int n_in, void* d_out, int out_size) {
  static Params P;
  static int nc = 0;
  static const void* cached[11];
  bool same = nc > 0 && cached[10] == d_out;
  for (int i = 0; i < 10 && same; i++) same = cached[i] == d_in[i];
  if (!same) {
    void* fn = nullptr;
    cudaDriverEntryPointQueryResult qr;
    cudaGetDriverEntryPoint("cuTensorMapEncodeTiled", &fn, cudaEnableDefault, &qr);
    EncodeFn enc = (EncodeFn)fn;
    void* act = nullptr;
    cudaGetSymbolAddress(&act, g_act);
    make_map(enc, &P.act128, act, S_LEN, ACT_W, 128);
    make_map(enc, &P.act64, act, S_LEN, ACT_W, 64);
    make_map(enc, &P.x128, d_in[0], S_LEN, DM, 128);
    make_map(enc, &P.ckv128, d_in[1], S_LEN, DM, 128);
    make_map(enc, &P.wq, d_in[2], DM, NH * HD, 128);
    make_map(enc, &P.wuk, d_in[3], DM, NH * HD, 128);
    make_map(enc, &P.wuv, d_in[4], DM, NH * HD, 128);
    make_map(enc, &P.wo, d_in[5], NH * HD, DM, 64);
    make_map(enc, &P.wg, d_in[7], DM, DFF, 128);
    make_map(enc, &P.wu, d_in[8], DM, DFF, 128);
    make_map(enc, &P.wd, d_in[9], DFF, DM, 64);
    make_map(enc, &P.out64, d_out, S_LEN, DM, 64);
    cudaFuncSetAttribute(fused_kernel, cudaFuncAttributeMaxDynamicSharedMemorySize, SMEM_BYTES);
    if (nc == 0) {
      cudaLaunchConfig_t cfg = {};
      cfg.gridDim = dim3(2 * MAXC); cfg.blockDim = dim3(384); cfg.dynamicSmemBytes = SMEM_BYTES;
      cudaLaunchAttribute at[1];
      at[0].id = cudaLaunchAttributeClusterDimension;
      at[0].val.clusterDim.x = 2; at[0].val.clusterDim.y = 1; at[0].val.clusterDim.z = 1;
      cfg.attrs = at; cfg.numAttrs = 1;
      int n = 0;
      if (cudaOccupancyMaxActiveClusters(&n, fused_kernel, &cfg) != cudaSuccess || n <= 0) { n = MAXC; (void)cudaGetLastError(); }
      nc = n < MAXC ? n : MAXC;
      build_schedule(P, nc);
    }
    for (int i = 0; i < 10; i++) cached[i] = d_in[i];
    cached[10] = d_out;
  }
  fused_kernel<<<2 * nc, 384, SMEM_BYTES>>>(P);
}
```

```cpp
#include <cuda_runtime.h>
#include <cuda_bf16.h>
#include <cuda.h>
#include <stdint.h>
#include <string.h>
#include <stdio.h>

namespace {

constexpr int S_LEN = 2048, DM = 512, NH = 32, HD = 128, DFF = 1792;
constexpr int ACT_K = 0, ACT_V = 4096, ACT_H = 8192, ACT_W = ACT_H + DFF;
constexpr size_t Q_OFF = (size_t)S_LEN * ACT_W, G_OFF = Q_OFF + (size_t)S_LEN * NH * HD, ACT_TOTAL = G_OFF + (size_t)S_LEN * DM;
constexpr int NSLOT = 6, SLOT = 32768, STAGE2 = 49152;
constexpr int STG_OFF = NSLOT * SLOT;
constexpr int BAR_OFF = STG_OFF + 32768;
constexpr int OUTB_OFF = BAR_OFF + 256;
constexpr int SMEM_BYTES = OUTB_OFF + 64 + 1024;
constexpr int MAXC = 66, P1LEN = 40, P2LEN = 16;
constexpr uint32_t PFC = 6;
constexpr uint32_t CTX_FAR = 20;
constexpr uint32_t XLATE = 10;
#define LAGD 4
#define LAGO 3
#define PRE_C 1
constexpr int PF1 = 2, PF2 = 16;
constexpr int FL_HEAD = 0, FL_H = 32, FL_CTX = 64, FL_G = 320, FL_DONE = 384, FL_TOTAL = 416;
constexpr uint32_t HEAD_CNT = 96, CTX_CNT = 4, G_CNT = 4;
constexpr uint32_t H_SPLIT = 24;
constexpr uint32_t ROLE_D = 16, ROLE_O = 32;

struct Params {
  uint8_t first[MAXC][2];
  uint8_t n2[MAXC];
  uint8_t role[MAXC];
  int nctas;
  uint32_t zero;
  CUtensorMap act128, act64, wq, wuk, wuv, wg, wu, wo, wd, x128, ckv128, x64, out64, ctx3;
  uint8_t p1[MAXC][P1LEN];
  uint8_t oh[8][NH];
  uint8_t p2[MAXC][P2LEN];
  uint16_t last[MAXC][P2LEN];
};

__device__ __align__(1024) __nv_bfloat16 g_act[ACT_TOTAL];
__device__ uint32_t g_flags[FL_TOTAL];

__device__ __forceinline__ uint32_t smem_u32(const void* p) { return (uint32_t)__cvta_generic_to_shared(p); }
__device__ __forceinline__ void mbar_init(uint32_t bar, uint32_t cnt) { asm volatile("mbarrier.init.shared::cta.b64 [%0], %1;" :: "r"(bar), "r"(cnt)); }
__device__ __forceinline__ void mbar_expect_tx(uint32_t bar, uint32_t bytes) { asm volatile("mbarrier.arrive.expect_tx.shared::cta.b64 _, [%0], %1;" :: "r"(bar), "r"(bytes) : "memory"); }
__device__ __forceinline__ void mbar_arrive(uint32_t bar) { asm volatile("mbarrier.arrive.shared::cta.b64 _, [%0];" :: "r"(bar) : "memory"); }
__device__ __forceinline__ void mbar_arrive_cluster(uint32_t remote_bar) { asm volatile("mbarrier.arrive.shared::cluster.b64 _, [%0];" :: "r"(remote_bar) : "memory"); }
__device__ __forceinline__ uint32_t mapa(uint32_t addr, uint32_t cta) { uint32_t r; asm("mapa.shared::cluster.u32 %0, %1, %2;" : "=r"(r) : "r"(addr), "r"(cta)); return r; }
__device__ __forceinline__ bool mbar_try(uint32_t bar, uint32_t parity) {
  uint32_t ok;
  asm volatile("{ .reg .pred p; mbarrier.try_wait.parity.shared::cta.b64 p, [%1], %2; selp.u32 %0, 1, 0, p; }" : "=r"(ok) : "r"(bar), "r"(parity) : "memory");
  return ok;
}
__device__ __forceinline__ uint32_t mbar_test(uint32_t bar, uint32_t parity) {
  uint32_t ok;
  asm volatile("{ .reg .pred p; mbarrier.test_wait.parity.shared::cta.b64 p, [%1], %2; selp.u32 %0, 1, 0, p; }" : "=r"(ok) : "r"(bar), "r"(parity) : "memory");
  return ok;
}
__device__ __forceinline__ void mbar_wait(uint32_t bar, uint32_t parity) {
  asm volatile("{ .reg .pred p;\n"
               "WAIT_%=: mbarrier.try_wait.parity.shared::cta.b64 p, [%0], %1;\n"
               "@!p bra WAIT_%=; }" :: "r"(bar), "r"(parity) : "memory");
}
constexpr uint64_t L2_NORMAL = 0x1000000000000000ull, L2_FIRST = 0x12F0000000000000ull;
__device__ __forceinline__ void tma_load(uint32_t dst, const CUtensorMap* m, int c0, int c1, uint32_t bar, uint64_t pol = L2_NORMAL) {
  asm volatile("cp.async.bulk.tensor.2d.shared::cluster.global.mbarrier::complete_tx::bytes.L2::cache_hint [%0], [%1, {%3, %4}], [%2], %5;"
    :: "r"(dst), "l"(m), "r"(bar), "r"(c0), "r"(c1), "l"(pol) : "memory");
}
__device__ __forceinline__ void tma_load_mc(uint32_t dst, const CUtensorMap* m, int c0, int c1, uint32_t bar, uint64_t pol = L2_NORMAL) {
  asm volatile("cp.async.bulk.tensor.2d.shared::cluster.global.mbarrier::complete_tx::bytes.multicast::cluster.L2::cache_hint [%0], [%1, {%3, %4}], [%2], %5, %6;"
    :: "r"(dst), "l"(m), "r"(bar), "r"(c0), "r"(c1), "h"((uint16_t)3), "l"(pol) : "memory");
}
__device__ __forceinline__ void tma_load3(uint32_t dst, const CUtensorMap* m, int c1, int c2, uint32_t bar, uint64_t pol) {
  asm volatile("cp.async.bulk.tensor.3d.shared::cluster.global.mbarrier::complete_tx::bytes.L2::cache_hint [%0], [%1, {%3, %4, %5}], [%2], %6;"
    :: "r"(dst), "l"(m), "r"(bar), "r"(0), "r"(c1), "r"(c2), "l"(pol) : "memory");
}
__device__ __forceinline__ bool elect() {
  uint32_t e;
  asm volatile("{ .reg .pred p; elect.sync _|p, 0xffffffff; selp.u32 %0, 1, 0, p; }" : "=r"(e));
  return e;
}
__device__ __forceinline__ void tma_store(const CUtensorMap* m, uint32_t src, int c0, int c1, uint64_t pol = L2_NORMAL) {
  asm volatile("cp.async.bulk.tensor.2d.global.shared::cta.bulk_group.L2::cache_hint [%0, {%2, %3}], [%1], %4;"
    :: "l"(m), "r"(src), "r"(c0), "r"(c1), "l"(pol) : "memory");
}
__device__ __forceinline__ void bulk_store(void* dst, uint32_t src, uint32_t bytes, uint64_t pol = L2_NORMAL) {
  asm volatile("cp.async.bulk.global.shared::cta.bulk_group.L2::cache_hint [%0], [%1], %2, %3;" :: "l"(dst), "r"(src), "r"(bytes), "l"(pol) : "memory");
}
__device__ __forceinline__ void bulk_load(uint32_t dst, const void* src, uint32_t bytes, uint32_t bar, uint64_t pol = L2_NORMAL) {
  asm volatile("cp.async.bulk.shared::cluster.global.mbarrier::complete_tx::bytes.L2::cache_hint [%0], [%1], %2, [%3], %4;" :: "r"(dst), "l"(src), "r"(bytes), "r"(bar), "l"(pol) : "memory");
}
__device__ __forceinline__ void sts4(uint32_t addr, uint32_t r0, uint32_t r1, uint32_t r2, uint32_t r3) {
  asm volatile("st.shared.v4.b32 [%0], {%1, %2, %3, %4};" :: "r"(addr), "r"(r0), "r"(r1), "r"(r2), "r"(r3) : "memory");
}
__device__ __forceinline__ void lds4(uint32_t& r0, uint32_t& r1, uint32_t& r2, uint32_t& r3, uint32_t addr) {
  asm volatile("ld.shared.v4.b32 {%0, %1, %2, %3}, [%4];" : "=r"(r0), "=r"(r1), "=r"(r2), "=r"(r3) : "r"(addr) : "memory");
}
__device__ __forceinline__ void ldg4(uint32_t& r0, uint32_t& r1, uint32_t& r2, uint32_t& r3, const void* p) {
  asm volatile("ld.global.ca.v4.b32 {%0, %1, %2, %3}, [%4];" : "=r"(r0), "=r"(r1), "=r"(r2), "=r"(r3) : "l"(p) : "memory");
}
__device__ __forceinline__ void ld4(uint32_t& r0, uint32_t& r1, uint32_t& r2, uint32_t& r3, const void* p) {
  asm volatile("ld.v4.b32 {%0, %1, %2, %3}, [%4];" : "=r"(r0), "=r"(r1), "=r"(r2), "=r"(r3) : "l"(p) : "memory");
}
__device__ __forceinline__ void bulk_commit() { asm volatile("cp.async.bulk.commit_group;" ::: "memory"); }
__device__ __forceinline__ void bulk_wait_read() { asm volatile("cp.async.bulk.wait_group.read 0;" ::: "memory"); }
__device__ __forceinline__ void bulk_wait_all() { asm volatile("cp.async.bulk.wait_group 0;" ::: "memory"); }
__device__ __forceinline__ void fence_async_smem() { asm volatile("fence.proxy.async.shared::cta;" ::: "memory"); }
__device__ __forceinline__ void fence_async_global() { asm volatile("fence.proxy.async.global;" ::: "memory"); }
__device__ __forceinline__ void sts_release(uint32_t addr, uint32_t v) { asm volatile("st.release.cta.shared::cta.u32 [%0], %1;" :: "r"(addr), "r"(v) : "memory"); }
__device__ __forceinline__ uint32_t lds_acquire(uint32_t addr) { uint32_t v; asm volatile("ld.acquire.cta.shared::cta.u32 %0, [%1];" : "=r"(v) : "r"(addr) : "memory"); return v; }
__device__ __forceinline__ void cluster_arrive() { __syncwarp(); asm volatile("barrier.cluster.arrive.relaxed.aligned;" ::: "memory"); }
__device__ __forceinline__ void cluster_wait() { asm volatile("barrier.cluster.wait.acquire.aligned;" ::: "memory"); }
__device__ __forceinline__ uint32_t cluster_rank() { uint32_t r; asm volatile("mov.u32 %0, %%cluster_ctarank;" : "=r"(r)); return r; }
__device__ __forceinline__ unsigned long long gtime() { unsigned long long t; asm volatile("mov.u64 %0, %%globaltimer;" : "=l"(t)); return t; }
__device__ __forceinline__ uint32_t clk() { uint32_t t; asm volatile("mov.u32 %0, %%clock;" : "=r"(t) :: "memory"); return t; }
__device__ __forceinline__ void tma_prefetch(const CUtensorMap* m, int c0, int c1) {
  asm volatile("cp.async.bulk.prefetch.tensor.2d.L2.global.tile [%0, {%1, %2}];" :: "l"(m), "r"(c0), "r"(c1) : "memory");
}
__device__ __forceinline__ void tma_prefetch3(const CUtensorMap* m, int c1, int c2) {
  asm volatile("cp.async.bulk.prefetch.tensor.3d.L2.global.tile [%0, {%1, %2, %3}];" :: "l"(m), "r"(0), "r"(c1), "r"(c2) : "memory");
}
__device__ __forceinline__ void wg_fence() { asm volatile("wgmma.fence.sync.aligned;" ::: "memory"); }
__device__ __forceinline__ void wg_commit() { asm volatile("wgmma.commit_group.sync.aligned;" ::: "memory"); }
template <int N> __device__ __forceinline__ void wg_wait() { asm volatile("wgmma.wait_group.sync.aligned %0;" :: "n"(N) : "memory"); }
template <int N> __device__ __forceinline__ void pin(float (&d)[N]) {
#pragma unroll
  for (int i = 0; i < N; i++) asm volatile("" : "+f"(d[i]) :: "memory");
}
template <int N> __device__ __forceinline__ void pinu(uint32_t (&d)[N]) {
#pragma unroll
  for (int i = 0; i < N; i++) asm volatile("" : "+r"(d[i]));
}
template <int ID> __device__ __forceinline__ void bar_sync(int n) { asm volatile("bar.sync %0, %1;" :: "n"(ID), "r"(n) : "memory"); }
template <int ID> __device__ __forceinline__ void bar_arrive(int n) { asm volatile("bar.arrive %0, %1;" :: "n"(ID), "r"(n) : "memory"); }
__device__ __forceinline__ void ldsm4(uint32_t& r0, uint32_t& r1, uint32_t& r2, uint32_t& r3, uint32_t addr) {
  asm volatile("ldmatrix.sync.aligned.m8n8.x4.shared.b16 {%0, %1, %2, %3}, [%4];" : "=r"(r0), "=r"(r1), "=r"(r2), "=r"(r3) : "r"(addr) : "memory");
}
__device__ __forceinline__ void stsm4(uint32_t addr, uint32_t r0, uint32_t r1, uint32_t r2, uint32_t r3) {
  asm volatile("stmatrix.sync.aligned.m8n8.x4.shared.b16 [%0], {%1, %2, %3, %4};" :: "r"(addr), "r"(r0), "r"(r1), "r"(r2), "r"(r3) : "memory");
}
__device__ __forceinline__ void stg4_if(uint32_t on, void* p, uint32_t r0, uint32_t r1, uint32_t r2, uint32_t r3) {
  asm volatile("{ .reg .pred p; setp.ne.u32 p, %5, 0; @p st.global.v4.b32 [%0], {%1, %2, %3, %4}; }"
               :: "l"(p), "r"(r0), "r"(r1), "r"(r2), "r"(r3), "r"(on) : "memory");
}
__device__ __forceinline__ uint32_t pack_bf16(float lo, float hi) {
  uint32_t r; asm("cvt.rn.bf16x2.f32 %0, %1, %2;" : "=r"(r) : "f"(hi), "f"(lo)); return r;
}
__device__ __forceinline__ uint32_t sub_bf16x2(uint32_t a, uint32_t b) { uint32_t r; asm("sub.rn.bf16x2 %0, %1, %2;" : "=r"(r) : "r"(a), "r"(b)); return r; }
__device__ __forceinline__ uint32_t add_bf16x2(uint32_t a, uint32_t b) { uint32_t r; asm("add.rn.bf16x2 %0, %1, %2;" : "=r"(r) : "r"(a), "r"(b)); return r; }
__device__ __forceinline__ uint32_t mul_bf16x2(uint32_t a, uint32_t b) { uint32_t r; asm("mul.rn.bf16x2 %0, %1, %2;" : "=r"(r) : "r"(a), "r"(b)); return r; }
__device__ __forceinline__ float bf_lo(uint32_t v) { return __uint_as_float(v << 16); }
__device__ __forceinline__ float bf_hi(uint32_t v) { return __uint_as_float(v & 0xFFFF0000u); }
__device__ __forceinline__ float ex2(float x) { float r; asm("ex2.approx.ftz.f32 %0, %1;" : "=f"(r) : "f"(x)); return r; }
__device__ __forceinline__ float rcp(float x) { float r; asm("rcp.approx.ftz.f32 %0, %1;" : "=f"(r) : "f"(x)); return r; }
__device__ __forceinline__ uint32_t ld_acquire(const uint32_t* p) { uint32_t v; asm volatile("ld.acquire.gpu.global.u32 %0, [%1];" : "=r"(v) : "l"(p) : "memory"); return v; }
__device__ __forceinline__ void red_release(uint32_t* p) { asm volatile("red.release.gpu.global.add.u32 [%0], 1;" :: "l"(p) : "memory"); }
__device__ __forceinline__ uint64_t mkdesc(uint32_t addr, uint32_t lbo, uint32_t sbo) {
  return (uint64_t)((addr & 0x3FFFF) >> 4) | ((uint64_t)(lbo >> 4) << 16) | ((uint64_t)(sbo >> 4) << 32) | (1ull << 62);
}

__device__ __forceinline__ void wgmma_rs_n128_kmaj(float (&d)[64], uint32_t a0, uint32_t a1, uint32_t a2, uint32_t a3, uint64_t db, int scale_d) {
  asm volatile("{ .reg .pred p; setp.ne.b32 p, %69, 0;\n"
      "wgmma.mma_async.sync.aligned.m64n128k16.f32.bf16.bf16 {"
      "%0, %1, %2, %3, %4, %5, %6, %7, %8, %9, %10, %11, %12, %13, %14, %15, "
      "%16, %17, %18, %19, %20, %21, %22, %23, %24, %25, %26, %27, %28, %29, %30, %31, "
      "%32, %33, %34, %35, %36, %37, %38, %39, %40, %41, %42, %43, %44, %45, %46, %47, "
      "%48, %49, %50, %51, %52, %53, %54, %55, %56, %57, %58, %59, %60, %61, %62, %63}, "
      "{%64, %65, %66, %67}, %68, p, 1, 1, 0; }\n"
    : "+f"(d[0]), "+f"(d[1]), "+f"(d[2]), "+f"(d[3]), "+f"(d[4]), "+f"(d[5]), "+f"(d[6]), "+f"(d[7]),
      "+f"(d[8]), "+f"(d[9]), "+f"(d[10]), "+f"(d[11]), "+f"(d[12]), "+f"(d[13]), "+f"(d[14]), "+f"(d[15]),
      "+f"(d[16]), "+f"(d[17]), "+f"(d[18]), "+f"(d[19]), "+f"(d[20]), "+f"(d[21]), "+f"(d[22]), "+f"(d[23]),
      "+f"(d[24]), "+f"(d[25]), "+f"(d[26]), "+f"(d[27]), "+f"(d[28]), "+f"(d[29]), "+f"(d[30]), "+f"(d[31]),
      "+f"(d[32]), "+f"(d[33]), "+f"(d[34]), "+f"(d[35]), "+f"(d[36]), "+f"(d[37]), "+f"(d[38]), "+f"(d[39]),
      "+f"(d[40]), "+f"(d[41]), "+f"(d[42]), "+f"(d[43]), "+f"(d[44]), "+f"(d[45]), "+f"(d[46]), "+f"(d[47]),
      "+f"(d[48]), "+f"(d[49]), "+f"(d[50]), "+f"(d[51]), "+f"(d[52]), "+f"(d[53]), "+f"(d[54]), "+f"(d[55]),
      "+f"(d[56]), "+f"(d[57]), "+f"(d[58]), "+f"(d[59]), "+f"(d[60]), "+f"(d[61]), "+f"(d[62]), "+f"(d[63])
    : "r"(a0), "r"(a1), "r"(a2), "r"(a3), "l"(db), "r"(scale_d));
}
__device__ __forceinline__ void wgmma_rs_n128_nmaj(float (&d)[64], uint32_t a0, uint32_t a1, uint32_t a2, uint32_t a3, uint64_t db, int scale_d) {
  asm volatile("{ .reg .pred p; setp.ne.b32 p, %69, 0;\n"
      "wgmma.mma_async.sync.aligned.m64n128k16.f32.bf16.bf16 {"
      "%0, %1, %2, %3, %4, %5, %6, %7, %8, %9, %10, %11, %12, %13, %14, %15, "
      "%16, %17, %18, %19, %20, %21, %22, %23, %24, %25, %26, %27, %28, %29, %30, %31, "
      "%32, %33, %34, %35, %36, %37, %38, %39, %40, %41, %42, %43, %44, %45, %46, %47, "
      "%48, %49, %50, %51, %52, %53, %54, %55, %56, %57, %58, %59, %60, %61, %62, %63}, "
      "{%64, %65, %66, %67}, %68, p, 1, 1, 1; }\n"
    : "+f"(d[0]), "+f"(d[1]), "+f"(d[2]), "+f"(d[3]), "+f"(d[4]), "+f"(d[5]), "+f"(d[6]), "+f"(d[7]),
      "+f"(d[8]), "+f"(d[9]), "+f"(d[10]), "+f"(d[11]), "+f"(d[12]), "+f"(d[13]), "+f"(d[14]), "+f"(d[15]),
      "+f"(d[16]), "+f"(d[17]), "+f"(d[18]), "+f"(d[19]), "+f"(d[20]), "+f"(d[21]), "+f"(d[22]), "+f"(d[23]),
      "+f"(d[24]), "+f"(d[25]), "+f"(d[26]), "+f"(d[27]), "+f"(d[28]), "+f"(d[29]), "+f"(d[30]), "+f"(d[31]),
      "+f"(d[32]), "+f"(d[33]), "+f"(d[34]), "+f"(d[35]), "+f"(d[36]), "+f"(d[37]), "+f"(d[38]), "+f"(d[39]),
      "+f"(d[40]), "+f"(d[41]), "+f"(d[42]), "+f"(d[43]), "+f"(d[44]), "+f"(d[45]), "+f"(d[46]), "+f"(d[47]),
      "+f"(d[48]), "+f"(d[49]), "+f"(d[50]), "+f"(d[51]), "+f"(d[52]), "+f"(d[53]), "+f"(d[54]), "+f"(d[55]),
      "+f"(d[56]), "+f"(d[57]), "+f"(d[58]), "+f"(d[59]), "+f"(d[60]), "+f"(d[61]), "+f"(d[62]), "+f"(d[63])
    : "r"(a0), "r"(a1), "r"(a2), "r"(a3), "l"(db), "r"(scale_d));
}
__device__ __forceinline__ void wgmma_rs_n64_kmaj(float (&d)[32], uint32_t a0, uint32_t a1, uint32_t a2, uint32_t a3, uint64_t db, int scale_d) {
  asm volatile("{ .reg .pred p; setp.ne.b32 p, %37, 0;\n"
      "wgmma.mma_async.sync.aligned.m64n64k16.f32.bf16.bf16 {"
      "%0, %1, %2, %3, %4, %5, %6, %7, %8, %9, %10, %11, %12, %13, %14, %15, "
      "%16, %17, %18, %19, %20, %21, %22, %23, %24, %25, %26, %27, %28, %29, %30, %31}, "
      "{%32, %33, %34, %35}, %36, p, 1, 1, 0; }\n"
    : "+f"(d[0]), "+f"(d[1]), "+f"(d[2]), "+f"(d[3]), "+f"(d[4]), "+f"(d[5]), "+f"(d[6]), "+f"(d[7]),
      "+f"(d[8]), "+f"(d[9]), "+f"(d[10]), "+f"(d[11]), "+f"(d[12]), "+f"(d[13]), "+f"(d[14]), "+f"(d[15]),
      "+f"(d[16]), "+f"(d[17]), "+f"(d[18]), "+f"(d[19]), "+f"(d[20]), "+f"(d[21]), "+f"(d[22]), "+f"(d[23]),
      "+f"(d[24]), "+f"(d[25]), "+f"(d[26]), "+f"(d[27]), "+f"(d[28]), "+f"(d[29]), "+f"(d[30]), "+f"(d[31])
    : "r"(a0), "r"(a1), "r"(a2), "r"(a3), "l"(db), "r"(scale_d));
}
__device__ __forceinline__ void wgmma_ss_n256_nmaj(float (&d)[128], uint64_t da, uint64_t db, int scale_d) {
  asm volatile("{ .reg .pred p; setp.ne.b32 p, %130, 0;\n"
      "wgmma.mma_async.sync.aligned.m64n256k16.f32.bf16.bf16 {"
      "%0, %1, %2, %3, %4, %5, %6, %7, %8, %9, %10, %11, %12, %13, %14, %15, "
      "%16, %17, %18, %19, %20, %21, %22, %23, %24, %25, %26, %27, %28, %29, %30, %31, "
      "%32, %33, %34, %35, %36, %37, %38, %39, %40, %41, %42, %43, %44, %45, %46, %47, "
      "%48, %49, %50, %51, %52, %53, %54, %55, %56, %57, %58, %59, %60, %61, %62, %63, "
      "%64, %65, %66, %67, %68, %69, %70, %71, %72, %73, %74, %75, %76, %77, %78, %79, "
      "%80, %81, %82, %83, %84, %85, %86, %87, %88, %89, %90, %91, %92, %93, %94, %95, "
      "%96, %97, %98, %99, %100, %101, %102, %103, %104, %105, %106, %107, %108, %109, %110, %111, "
      "%112, %113, %114, %115, %116, %117, %118, %119, %120, %121, %122, %123, %124, %125, %126, %127}, "
      "%128, %129, p, 1, 1, 0, 1; }\n"
    : "+f"(d[0]), "+f"(d[1]), "+f"(d[2]), "+f"(d[3]), "+f"(d[4]), "+f"(d[5]), "+f"(d[6]), "+f"(d[7]),
      "+f"(d[8]), "+f"(d[9]), "+f"(d[10]), "+f"(d[11]), "+f"(d[12]), "+f"(d[13]), "+f"(d[14]), "+f"(d[15]),
      "+f"(d[16]), "+f"(d[17]), "+f"(d[18]), "+f"(d[19]), "+f"(d[20]), "+f"(d[21]), "+f"(d[22]), "+f"(d[23]),
      "+f"(d[24]), "+f"(d[25]), "+f"(d[26]), "+f"(d[27]), "+f"(d[28]), "+f"(d[29]), "+f"(d[30]), "+f"(d[31]),
      "+f"(d[32]), "+f"(d[33]), "+f"(d[34]), "+f"(d[35]), "+f"(d[36]), "+f"(d[37]), "+f"(d[38]), "+f"(d[39]),
      "+f"(d[40]), "+f"(d[41]), "+f"(d[42]), "+f"(d[43]), "+f"(d[44]), "+f"(d[45]), "+f"(d[46]), "+f"(d[47]),
      "+f"(d[48]), "+f"(d[49]), "+f"(d[50]), "+f"(d[51]), "+f"(d[52]), "+f"(d[53]), "+f"(d[54]), "+f"(d[55]),
      "+f"(d[56]), "+f"(d[57]), "+f"(d[58]), "+f"(d[59]), "+f"(d[60]), "+f"(d[61]), "+f"(d[62]), "+f"(d[63]),
      "+f"(d[64]), "+f"(d[65]), "+f"(d[66]), "+f"(d[67]), "+f"(d[68]), "+f"(d[69]), "+f"(d[70]), "+f"(d[71]),
      "+f"(d[72]), "+f"(d[73]), "+f"(d[74]), "+f"(d[75]), "+f"(d[76]), "+f"(d[77]), "+f"(d[78]), "+f"(d[79]),
      "+f"(d[80]), "+f"(d[81]), "+f"(d[82]), "+f"(d[83]), "+f"(d[84]), "+f"(d[85]), "+f"(d[86]), "+f"(d[87]),
      "+f"(d[88]), "+f"(d[89]), "+f"(d[90]), "+f"(d[91]), "+f"(d[92]), "+f"(d[93]), "+f"(d[94]), "+f"(d[95]),
      "+f"(d[96]), "+f"(d[97]), "+f"(d[98]), "+f"(d[99]), "+f"(d[100]), "+f"(d[101]), "+f"(d[102]), "+f"(d[103]),
      "+f"(d[104]), "+f"(d[105]), "+f"(d[106]), "+f"(d[107]), "+f"(d[108]), "+f"(d[109]), "+f"(d[110]), "+f"(d[111]),
      "+f"(d[112]), "+f"(d[113]), "+f"(d[114]), "+f"(d[115]), "+f"(d[116]), "+f"(d[117]), "+f"(d[118]), "+f"(d[119]),
      "+f"(d[120]), "+f"(d[121]), "+f"(d[122]), "+f"(d[123]), "+f"(d[124]), "+f"(d[125]), "+f"(d[126]), "+f"(d[127])
    : "l"(da), "l"(db), "r"(scale_d));
}

struct Cur {
  uint32_t s, p;
  __device__ __forceinline__ void next() { if (++s == NSLOT) { s = 0; p ^= 1; } }
};

struct Ctx {
  uint32_t base;
  uint32_t rel;
  uint32_t lane;
  __device__ __forceinline__ uint32_t full(uint32_t s) const { return base + BAR_OFF + s * 8; }
  __device__ __forceinline__ uint32_t empty(uint32_t s) const { return base + BAR_OFF + 64 + s * 8; }
  __device__ __forceinline__ uint32_t stg_full(uint32_t w) const { return base + BAR_OFF + 128 + w * 8; }
  __device__ __forceinline__ uint32_t stg_empty(uint32_t w) const { return base + BAR_OFF + 144 + w * 8; }
  __device__ __forceinline__ uint32_t done_bar() const { return base + BAR_OFF + 160; }
  __device__ __forceinline__ uint32_t dep_cnt() const { return base + BAR_OFF + 168; }
  __device__ __forceinline__ uint32_t dep_use() const { return base + BAR_OFF + 172; }
  __device__ __forceinline__ uint32_t g2_pos() const { return base + BAR_OFF + 240; }
  __device__ __forceinline__ uint32_t g_full(uint32_t w) const { return base + BAR_OFF + 48 + w * 8; }
  __device__ __forceinline__ uint32_t out_full(uint32_t w, uint32_t q) const { return base + OUTB_OFF + w * 32 + q * 8; }
  __device__ __forceinline__ uint32_t epoch() const { return base + BAR_OFF + 244; }
  __device__ __forceinline__ uint32_t full2(uint32_t s) const { return base + BAR_OFF + 176 + s * 8; }
  __device__ __forceinline__ uint32_t empty2(uint32_t s) const { return base + BAR_OFF + 208 + s * 8; }
  __device__ __forceinline__ uint32_t stage(uint32_t s) const { return base + s * STAGE2; }
  __device__ __forceinline__ void release2(uint32_t s) const { if (lane < 2) mbar_arrive_cluster(rel + (208 - 64) + s * 8); }
  __device__ __forceinline__ uint32_t slot(uint32_t s) const { return base + s * SLOT; }
  __device__ __forceinline__ void wait_full(const Cur& c) const { mbar_wait(full(c.s), c.p); }
  __device__ __forceinline__ void wait_stg(uint32_t w, uint32_t ph) const { mbar_wait(stg_empty(w), ph); }
  __device__ __forceinline__ void order_wait(uint32_t wg) const { if (wg) bar_sync<2>(256); else bar_sync<1>(256); }
  __device__ __forceinline__ void dump(int) const {}
  __device__ __forceinline__ void release(uint32_t s) const { if (lane < 2) mbar_arrive_cluster(rel + s * 8); }
  __device__ __forceinline__ void release_dep(uint32_t s, uint32_t dep) const { if (lane < 2) mbar_arrive_cluster(rel + s * 8 + dep); }
};

__device__ __forceinline__ void wait_dep(const Ctx& X, uint32_t k) {
  while (lds_acquire(X.dep_cnt()) <= k) __nanosleep(20);
}
__device__ __forceinline__ void wait_flag(const Ctx& X, uint32_t k, uint32_t f, uint32_t cnt) {
  while (lds_acquire(X.dep_cnt()) <= k) {
    const uint32_t e = lds_acquire(X.epoch());
    if (e && (int32_t)(ld_acquire(&g_flags[f]) - e * cnt) >= 0) { fence_async_global(); break; }
  }
  __syncwarp();
}

#define TS(i)

#define LX(f)

__device__ __forceinline__ uint32_t first_stage(uint32_t ring_pos) { return ring_pos == 0 ? 0u : (ring_pos <= 3 ? 2u : 3u); }

__device__ __forceinline__ const CUtensorMap* slice_src(const Params& P, uint32_t op, uint32_t rank, int& col) {
  if (op < 96) { col = (op & 31) * 128 + rank * 64; return op < 32 ? &P.wuk : (op < 64 ? &P.wuv : &P.wq); }
  col = (op - 96) * 64;
  return rank ? &P.wu : &P.wg;
}
__device__ __forceinline__ void prefetch_w2(const Params& P, uint32_t role, uint32_t rank, int s) {
  if ((s & 7) == ((role >> 1) & 7) && s < ((role & ROLE_D) ? 28 : 2 * NH)) {
    const CUtensorMap* m = (role & ROLE_D) ? &P.wd : &P.wo;
    const int col = (role & 1) * 256 + rank * 128;
    tma_prefetch(m, col, s * 64);
    tma_prefetch(m, col + 64, s * 64);
  }
}
__device__ __forceinline__ void prefetch_w2_head(const Params& P, const Ctx& X, uint32_t role, uint32_t rank) {
  asm volatile("red.shared.max.u32 [%0], %1;" :: "r"(X.dep_use()), "r"(PFC) : "memory");
#pragma unroll 1
  for (int s = (role >> 1) & 7; s < PF2 && role; s += 8) prefetch_w2(P, role, rank, s);
}

__device__ __forceinline__ uint32_t half_first(uint32_t t, uint32_t n2, uint32_t w, uint32_t rank) {
  return (rank ^ (t ? t : n2 & w)) & 1;
}
__device__ __forceinline__ int item_row(uint32_t t, uint32_t n2, uint32_t it, uint32_t w, uint32_t rank) {
  return (int)((it & 7) * 256 + 192 - ((t ^ w) & 1) * 128 - half_first(t, n2, w, rank) * 64);
}
#define QMINJ 2
__device__ __forceinline__ bool q_staged(const Params& P, int cl, uint32_t t, uint32_t n2) {
  return t + 1 < n2 && (P.p2[cl][t] & 7) >= QMINJ && (t || P.p1[cl][0] != 0xFF);
}
__device__ __forceinline__ __nv_bfloat16* q_tile(uint32_t head, int row) { return g_act + Q_OFF + ((size_t)head * S_LEN + row) * HD; }

__device__ __forceinline__ void producer(const Params& P, const Ctx& X, int cl, uint32_t rank) {
  Cur c{0, 0};
  auto acquire = [&]() { mbar_wait(X.empty(c.s), c.p ^ 1); };
  const uint32_t n2 = P.n2[cl], role = P.role[cl];
  int arow = -1;
#pragma unroll 1
  for (int i = 0; i < P1LEN - 1; i++) {
    const uint32_t op = P.p1[cl][i];
    if (op == 0xFF) break;
    const bool isx = (op & 0x88) == 0x88;
    if (op & 0x80) {
      arow = (op & 7) * 256 + rank * 128;
      if (!isx) continue;
    }
    int col;
    const CUtensorMap* m = slice_src(P, op, rank, col);
#pragma unroll 1
    for (int k = 0; k < 4; k++) {
      if (arow >= 0) {
        if (i > 1 || c.p) {
          acquire();
          if (elect()) {
            mbar_expect_tx(X.full(c.s), SLOT);
            tma_load(X.slot(c.s), isx ? &P.x128 : &P.ckv128, k * 128, arow, X.full(c.s));
            tma_load(X.slot(c.s) + 16384, isx ? &P.x128 : &P.ckv128, k * 128 + 64, arow, X.full(c.s));
          }
        }
        c.next();
      }
      if (!isx) {
        if (i > 1 || c.p) {
          acquire();
          if (elect()) {
            mbar_expect_tx(X.full(c.s), SLOT);
            tma_load_mc(X.slot(c.s) + rank * 16384, m, col, k * 128, X.full(c.s));
          }
        }
        c.next();
      }
    }
    arow = -1;
  }
  if (n2) {
    auto load = [&](int col, int row, uint32_t last) {
      acquire();
      if (elect()) {
        mbar_expect_tx(X.full(c.s), SLOT);
        tma_load_mc(X.slot(c.s) + rank * 16384, &P.act128, col, row, X.full(c.s), (last & 1) ? L2_FIRST : L2_NORMAL);
      }
      c.next();
    };
    int vcol = 0, vrow = -1;
    uint32_t vlast = 0;
#pragma unroll 1
    for (uint32_t t = 0; t < n2; t++) {
      const uint32_t it = P.p2[cl][t];
      const int kcol = ACT_K + (it >> 3) * 128 + rank * 64;
      wait_flag(X, t, FL_HEAD + (it >> 3), HEAD_CNT);
      if (!t) {
        acquire();
        if (elect()) {
          mbar_expect_tx(X.full(c.s), SLOT);
          bulk_load(X.slot(c.s), q_tile(it >> 3, item_row(0, n2, it, 0, rank)), 16384, X.full(c.s));
          bulk_load(X.slot(c.s) + 16384, q_tile(it >> 3, item_row(0, n2, it, 1, rank)), 16384, X.full(c.s));
        }
        c.next();
      }
      if (t && elect()) {
        tma_prefetch3(&P.ctx3, rank * 64, it * 4);
        tma_prefetch3(&P.ctx3, rank * 64, it * 4 + 2);
        tma_prefetch(&P.act128, kcol, (it & 7) * 256);
        if (it & 7) tma_prefetch(&P.act128, kcol, (it & 7) * 256 - 128);
        tma_prefetch(&P.act128, kcol + ACT_V, (it & 7) * 256 + 128);
        tma_prefetch(&P.act128, kcol + ACT_V, (it & 7) * 256);
      }
#pragma unroll 1
      for (int row = (it & 7) * 256 + 128; row >= 0; row -= 128) {
        const uint32_t last = P.last[cl][t] >> (row >> 7);
        load(kcol, row, last);
        if (vrow >= 0) load(vcol, vrow, vlast);
        vcol = kcol + (ACT_V - ACT_K); vrow = row; vlast = last;
      }
    }
    load(vcol, vrow, vlast);
  }
  if (role) {
    const bool dn = role & ROLE_D;
    const int J = (role >> 1) & 7, nh = role & 1;
    const int row = J * 256 + rank * 128;
#define PL(i)
    uint32_t st = first_stage(c.s), ph = 0;
    sts_release(X.dep_use(), PFC);
#pragma unroll 1
    for (int s = 0; s < (dn ? 28 : 2 * NH); s++) {
      if (s < 4) {
        const uint32_t s0 = (st * 3) >> 1;
        mbar_wait(X.empty(s0), (s0 >= c.s ? c.p : c.p ^ 1) ^ 1);
        mbar_wait(X.empty(s0 + 1), (s0 + 1 >= c.s ? c.p : c.p ^ 1) ^ 1);
      } else {
        mbar_wait(X.empty2(st), ph ^ 1);
      }
      PL(0);
      const uint32_t dst = X.stage(st), bar = X.full2(st);
      const int ks = dn ? s : P.oh[J][s >> 1] * 2 + (s & 1);
      const CUtensorMap* m = dn ? &P.wd : &P.wo;
      if (elect()) {
        mbar_expect_tx(bar, STAGE2);
        tma_load_mc(dst + 16384 + rank * 16384, m, nh * 256 + rank * 128, ks * 64, bar);
        tma_load_mc(dst + 16384 + rank * 16384 + 8192, m, nh * 256 + rank * 128 + 64, ks * 64, bar);
      }
      PL(1);
      sts_release(X.g2_pos(), (s + 1) * 4 + st);
      if (dn) wait_dep(X, n2 + (s >= (int)H_SPLIT));
      else wait_flag(X, n2 + (s >> 1), FL_CTX + (ks >> 1) * 8 + J, CTX_CNT);
      PL(2);
      if (elect()) {
        if (dn) {
          tma_load(dst, &P.act128, ACT_H + ks * 64, row, bar, L2_FIRST);
        } else {
          tma_load3(dst, &P.ctx3, (ks & 1) * 64, (ks >> 1) * 32 + (row >> 6), bar, L2_FIRST);
        }
        prefetch_w2(P, role, rank, s + PF2);
      }
      PL(3);
      sts_release(X.dep_use(), (s >> 1) + 1 + PFC);
      if ((s & 3) == 3) ph ^= 1;
      st = (st + 1) & 3;
    }
  }
}

__device__ __forceinline__ void dep_warp(const Params& P, const Ctx& X, int cl, uint32_t rank) {
  const unsigned long long t0 = gtime();
  const uint32_t epoch1 = ld_acquire(&g_flags[FL_DONE]) / (uint32_t)P.nctas + 1;
  sts_release(X.epoch(), epoch1);
  asm volatile("red.relaxed.gpu.global.add.u32 [%0], 1;" :: "l"(&g_flags[FL_DONE]) : "memory");
  const uint32_t n2 = P.n2[cl], role = P.role[cl], J = (role >> 1) & 7;
  const uint32_t nd = n2 + ((role & ROLE_D) ? 2 : (role ? NH : 0));
#pragma unroll 1
  for (uint32_t k = 0; k < nd; k++) {
    uint32_t f, cnt;
    const bool is_ctx = k >= n2 && (role & ROLE_O);
    if (k < n2) { f = FL_HEAD + (P.p2[cl][k] >> 3); cnt = HEAD_CNT; }
    else if (role & ROLE_D) { f = FL_H + J + (k - n2) * 8; cnt = k > n2 ? (28 - H_SPLIT) * 4 : H_SPLIT * 4; }
    else { f = FL_CTX + P.oh[J][k - n2] * 8 + J; cnt = CTX_CNT; }
    while ((int32_t)(ld_acquire(&g_flags[f]) - epoch1 * cnt) < 0 ||
           (is_ctx && k - n2 >= lds_acquire(X.dep_use()))) {
      __nanosleep(32);
      if (gtime() - t0 > 4000000000ull) __trap();
    }
    fence_async_global();
    sts_release(X.dep_cnt(), k + 1);
    if (is_ctx) tma_prefetch3(&P.ctx3, (role & 1) * 64, (f - FL_CTX) * 4 + rank * 2);
  }
  while (!mbar_try(X.done_bar(), 0)) {
    if (gtime() - t0 > 4000000000ull) __trap();
  }
}

__device__ __forceinline__ void storer(const Params& P, const Ctx& X, int cl, uint32_t rank, uint32_t w) {
  uint32_t ph = 0;
  const uint32_t stg = X.base + STG_OFF + w * 16384;
  const uint32_t n2 = P.n2[cl], role = P.role[cl];
  auto get_x = [&](int col) {
    col += (role & 1) * 256;
    if (elect()) {
      mbar_expect_tx(X.stg_empty(w), 16384);
      tma_load(stg, &P.x64, col, ((role >> 1) & 7) * 256 + rank * 128 + w * 64, X.stg_empty(w));
      tma_load(stg + 8192, &P.x64, col + 64, ((role >> 1) & 7) * 256 + rank * 128 + w * 64, X.stg_empty(w));
    }
  };
  const uint32_t pfp = P.p1[cl][0] & 7;
  int pair = 0, t = -1;
#pragma unroll 1
  for (int i = 0; i < 64 && !__any_sync(0xffffffffu, mbar_try(X.full(1), 0)); i++) __nanosleep(32);
#pragma unroll 1
  for (int i = 1 - PF1;; i++) {
    int col, row, boxes = 2;
    uint32_t flag;
    bool last, far;
    if (t < 0) {
      const uint32_t nx = P.p1[cl][i + PF1 + 1];
      if (w == 0 && nx < 0x80 && ((i ^ (pfp >> 2)) & 1)) {
        const CUtensorMap* m = slice_src(P, nx, rank, col);
        if (elect()) tma_prefetch(m, col, (pfp & 3) * 128);
      }
      if (i < 0) continue;
      const uint32_t op = P.p1[cl][i];
      if (op == 0xFF) { t = 0; continue; }
      if (op & 0x80) { pair = op & 7; continue; }
      row = pair * 256 + rank * 128 + w * 64;
      last = n2 == 0 && P.p1[cl][i + 1] == 0xFF;
      far = op >= 96;
      if (op >= 96) { col = ACT_H + (op - 96) * 64; boxes = 1; flag = FL_H + pair + (op >= 96 + H_SPLIT ? 8 : 0); }
      else { col = op < 64 ? op * 128 : op - 64; boxes = op < 64 ? 2 : 0; flag = FL_HEAD + (op & 31); }
    } else {
      if (t >= (int)n2) break;
      const uint32_t it = P.p2[cl][t];
      last = t + 1 == (int)n2;
      far = it < CTX_FAR * 8;
      col = it >> 3; boxes = 0; row = item_row(t, n2, it, w, rank); flag = FL_CTX + it;
      t++;
    }
    if (w && elect()) {
      if (n2 == 0) {
        if (P.p1[cl][i + PFC] == 0xFF) asm volatile("red.shared.add.u32 [%0], %1;" :: "r"(X.dep_use()), "r"(1) : "memory");
        if (P.p1[cl][i + 4] == 0xFF && P.p1[cl][i + 3] != 0xFF) prefetch_w2(P, role, rank, (role >> 1) & 7);
        if (P.p1[cl][i + 2] == 0xFF && P.p1[cl][i + 1] != 0xFF) prefetch_w2(P, role, rank, ((role >> 1) & 7) + 8);
      } else if (last) {
        prefetch_w2_head(P, X, role, rank);
      }
    }
    const uint32_t u = t < 0 ? 0 : t, nx = P.p2[cl][u + 1];
    bool sq = (t >= 0 || P.p1[cl][i + 1] == 0xFF) && q_staged(P, cl, u, n2);
    const __nv_bfloat16* qn = q_tile(nx >> 3, item_row(u + 1, n2, nx, w, rank));
    auto get_q = [&]() {
      if (elect()) {
        mbar_expect_tx(X.stg_empty(w), 16384);
        bulk_load(stg, qn, 16384, X.stg_empty(w));
      }
    };
    mbar_wait(X.stg_full(w), ph);
    ph ^= 1;
#define LT(i)
    if (elect()) {
      LT(0);
      fence_async_smem();
      const uint64_t pol = far ? L2_FIRST : L2_NORMAL;
      if (boxes) {
        tma_store(&P.act64, stg, col, row, pol);
        if (boxes == 2) tma_store(&P.act64, stg + 8192, col + 64, row, pol);
      } else {
        bulk_store(q_tile(col, row), stg, 16384, pol);
      }
      bulk_commit();
      bulk_wait_read();
      LT(1);
      if (!sq && (!last || !(role & ROLE_O))) mbar_arrive(X.stg_empty(w));
    }
    __syncwarp();
    if (sq && __any_sync(0xffffffffu, lds_acquire(X.dep_cnt()) > u + 1)) { get_q(); sq = false; }
    if (elect()) {
      bulk_wait_all();
      red_release(&g_flags[flag]);
      LT(3);
    }
    __syncwarp();
    if (sq) { wait_dep(X, u + 1); __syncwarp(); get_q(); }
  }
  if (role & ROLE_O) {
    while (lds_acquire(X.g2_pos()) < (XLATE + (role & 15)) * 4) __nanosleep(200);
    __syncwarp();
    get_x(0);
    mbar_wait(X.stg_full(w), ph);
    get_x(128);
    mbar_wait(X.stg_full(w), ph ^ 1);
    uint32_t st = 0;
    if (X.lane == 0) {
      const uint32_t want = lds_acquire(X.epoch()) * G_CNT, gidx = (role & 15) * 4 + rank * 2 + w;
      while ((int32_t)(ld_acquire(&g_flags[FL_G + gidx]) - want) < 0) __nanosleep(64);
      fence_async_global();
      mbar_expect_tx(X.stg_empty(w), 16384);
      bulk_load(stg, g_act + G_OFF + gidx * 16384, 16384, X.stg_empty(w));
      uint32_t pos;
      while ((pos = lds_acquire(X.g2_pos())) < (2 * NH - 3) * 4) __nanosleep(100);
      st = (pos - (pos >> 2) + 1) & 3;
      asm volatile("prefetch.tensormap [%0];" :: "l"(&P.out64) : "memory");
      mbar_wait(X.empty2(st), 1);
      mbar_expect_tx(X.g_full(w), 16384);
      bulk_load(X.stage(st) + w * 16384, g_act + G_OFF + gidx * 16384 + 8192, 16384, X.g_full(w));
    }
    const uint32_t hi = X.stage(__shfl_sync(0xffffffffu, st, 0)) + w * 16384;
#pragma unroll 1
    for (uint32_t q = 0; q < 4; q++) {
      mbar_wait(X.out_full(w, q), 0);
      fence_async_smem();
      if (elect()) tma_store(&P.out64, (q & 2 ? hi : stg) + (q & 1) * 8192, (role & 1) * 256 + q * 64, ((role >> 1) & 7) * 256 + rank * 128 + w * 64);
    }
    bulk_commit();
    bulk_wait_read();
  }
}

struct Cons {
  uint32_t wg;
  uint32_t frag;
  uint32_t xr;
  uint32_t chi;
  uint32_t stg_ph;
};
#define LG(f)
#define LR(f)
#define LW(f)
#define LF(f)
#define LP(f)

__device__ __forceinline__ void order_pass(uint32_t wg) { if (wg) bar_arrive<1>(256); else bar_arrive<2>(256); }

__device__ __forceinline__ void stg_publish(const Ctx& X, Cons& C) {
  __syncwarp();
  if (X.lane == 0) mbar_arrive(X.stg_full(C.wg));
  C.stg_ph ^= 1;
}

__device__ __forceinline__ float gelu_mul(float g, float u) {
  const float k0 = -2.0f * 0.7978845608028654f * 1.4426950408889634f;
  const float k1 = k0 * 0.044715f;
  const float e = ex2(g * fmaf(g * g, k1, k0));
  return g * rcp(1.0f + e) * u;
}

constexpr float SM_SCALE = 0.08838834764831845f * 1.4426950408889634f;

__device__ __forceinline__ void phase1(const Params& P, const Ctx& X, Cons& C, Cur& c, int cl) {
  uint32_t a[128];
  float acc[64];
  float rs0 = 1.0f, rs1 = 1.0f;
  bool need_var = false, fuse = false;
  const uint32_t stg = X.base + STG_OFF + C.wg * 16384;
  for (int i = 0; i < P1LEN; i++) {
    const uint32_t op = P.p1[cl][i];
    if (op == 0xFF) break;
    auto load_a = [&](int k) {
      X.wait_full(c);
      LP(3);
      const uint32_t b = X.slot(c.s) + C.wg * 8192 + C.frag;
#pragma unroll
      for (int kk = 0; kk < 8; kk++) {
        const uint32_t ch = ((kk & 3) * 2 + C.chi) ^ C.xr;
        ldsm4(a[(k * 8 + kk) * 4], a[(k * 8 + kk) * 4 + 1], a[(k * 8 + kk) * 4 + 2], a[(k * 8 + kk) * 4 + 3], b + (kk >> 2) * 16384 + ch * 16);
      }
      X.release_dep(c.s, (a[k * 32] ^ a[k * 32 + 4] ^ a[k * 32 + 8] ^ a[k * 32 + 12] ^ a[k * 32 + 16] ^ a[k * 32 + 20] ^ a[k * 32 + 24] ^ a[k * 32 + 28]) & P.zero);
      c.next();
    };
    if (op & 0x80) {
      rs0 = 1.0f; rs1 = 1.0f;
      need_var = (op & 8) != 0;
      fuse = !need_var;
      if (op & 8) {
        float s0 = 0.f, s1 = 0.f;
#pragma unroll
        for (int k = 0; k < 4; k++) {
          load_a(k);
#pragma unroll
          for (int r = k * 32; r < k * 32 + 32; r += 2) { s0 += bf_lo(a[r]) + bf_hi(a[r]); s1 += bf_lo(a[r + 1]) + bf_hi(a[r + 1]); }
        }
        s0 += __shfl_xor_sync(0xffffffffu, s0, 1); s1 += __shfl_xor_sync(0xffffffffu, s1, 1);
        s0 += __shfl_xor_sync(0xffffffffu, s0, 2); s1 += __shfl_xor_sync(0xffffffffu, s1, 2);
        s0 *= 1.0f / DM; s1 *= 1.0f / DM;
        const uint32_t mb0 = pack_bf16(s0, s0), mb1 = pack_bf16(s1, s1);
        rs0 = s0 - bf_lo(mb0); rs1 = s1 - bf_lo(mb1);
#pragma unroll
        for (int r = 0; r < 128; r += 2) { a[r] = sub_bf16x2(a[r], mb0); a[r + 1] = sub_bf16x2(a[r + 1], mb1); }
      }
      continue;
    }
    LP(4);
    LP(5);
    uint32_t prev = 0;
#pragma unroll
    for (int k = 0; k < 4; k++) {
      if (fuse) load_a(k);
      if (fuse || k == 0) X.order_wait(C.wg);
      X.wait_full(c);
      LP(6);
      const uint64_t db = mkdesc(X.slot(c.s), 16384, 1024);
      wg_fence();
#pragma unroll
      for (int kk = 0; kk < 8; kk++) {
        const int r = (k * 8 + kk) * 4;
        wgmma_rs_n128_nmaj(acc, a[r], a[r + 1], a[r + 2], a[r + 3], db + kk * 128, (k | kk) != 0);
      }
      wg_commit();
      if (fuse || k == 3) order_pass(C.wg);
      if (k > 0) { wg_wait<1>(); X.release(prev); }
      prev = c.s;
      c.next();
    }
    fuse = false;
    wg_wait<0>();
    pin(acc);
    LP(7);
    LF(12);
    X.release(prev);
    if (need_var) {
      need_var = false;
      float v0 = 0.f, v1 = 0.f, w0 = 0.f, w1 = 0.f;
#pragma unroll
      for (int r = 0; r < 128; r += 2) {
        v0 = fmaf(bf_lo(a[r]), bf_lo(a[r]), v0); w0 = fmaf(bf_hi(a[r]), bf_hi(a[r]), w0);
        v1 = fmaf(bf_lo(a[r + 1]), bf_lo(a[r + 1]), v1); w1 = fmaf(bf_hi(a[r + 1]), bf_hi(a[r + 1]), w1);
      }
      v0 += w0; v1 += w1;
      v0 += __shfl_xor_sync(0xffffffffu, v0, 1); v1 += __shfl_xor_sync(0xffffffffu, v1, 1);
      v0 += __shfl_xor_sync(0xffffffffu, v0, 2); v1 += __shfl_xor_sync(0xffffffffu, v1, 2);
      rs0 = 1.0f / sqrtf(fmaxf(v0 * (1.0f / DM) - rs0 * rs0, 0.f) + 1e-5f);
      rs1 = 1.0f / sqrtf(fmaxf(v1 * (1.0f / DM) - rs1 * rs1, 0.f) + 1e-5f);
    }
    if (op >= 64) {
      const float qs = op < 96 ? SM_SCALE : 1.0f;
      const float e0 = rs0 * qs, e1 = rs1 * qs;
#pragma unroll
      for (int j = 0; j < 16; j++) { acc[4 * j] *= e0; acc[4 * j + 1] *= e0; acc[4 * j + 2] *= e1; acc[4 * j + 3] *= e1; }
    }
    LP(8);
    X.wait_stg(C.wg, C.stg_ph ^ 1);
    LP(9);
    if (op >= 64 && op < 96) {
#pragma unroll
      for (int j = 0; j < 8; j++)
        sts4(stg + (threadIdx.x & 96) * 32 + (j >> 1) * 4096 + (j & 1) * 512 + X.lane * 16, pack_bf16(acc[8 * j], acc[8 * j + 1]), pack_bf16(acc[8 * j + 2], acc[8 * j + 3]),
             pack_bf16(acc[8 * j + 4], acc[8 * j + 5]), pack_bf16(acc[8 * j + 6], acc[8 * j + 7]));
    } else if (op < 64) {
#pragma unroll
      for (int j = 0; j < 8; j++) {
        const uint32_t ch = ((j & 3) * 2 + C.chi) ^ C.xr;
        stsm4(stg + (j >> 2) * 8192 + C.frag + ch * 16, pack_bf16(acc[8 * j], acc[8 * j + 1]), pack_bf16(acc[8 * j + 2], acc[8 * j + 3]),
              pack_bf16(acc[8 * j + 4], acc[8 * j + 5]), pack_bf16(acc[8 * j + 6], acc[8 * j + 7]));
      }
    } else {
#pragma unroll
      for (int j = 0; j < 4; j++) {
        float hv[8];
#pragma unroll
        for (int e = 0; e < 8; e++) hv[e] = gelu_mul(acc[8 * j + e], acc[32 + 8 * j + e]);
        const uint32_t ch = (j * 2 + C.chi) ^ C.xr;
        stsm4(stg + C.frag + ch * 16, pack_bf16(hv[0], hv[1]), pack_bf16(hv[2], hv[3]), pack_bf16(hv[4], hv[5]), pack_bf16(hv[6], hv[7]));
      }
    }
    stg_publish(X, C);
  }
}

__device__ __forceinline__ uint64_t desc64(uint32_t lo) { uint64_t d; asm("mov.b64 %0, {%1, %2};" : "=l"(d) : "r"(lo), "n"(0x40000040)); return d; }
__device__ __forceinline__ void issue_qk(float (&s)[64], const uint32_t (&q)[32], uint32_t kd) {
  wg_fence();
#pragma unroll
  for (int kk = 0; kk < 8; kk++)
    wgmma_rs_n128_kmaj(s, q[4 * kk], q[4 * kk + 1], q[4 * kk + 2], q[4 * kk + 3], desc64(kd + (kk >> 2) * 1024 + (kk & 3) * 2), kk != 0);
  wg_commit();
}
__device__ __forceinline__ void issue_qk(float (&s)[32], const uint32_t (&q)[32], uint32_t kd) {
  wg_fence();
#pragma unroll
  for (int kk = 0; kk < 8; kk++)
    wgmma_rs_n64_kmaj(s, q[4 * kk], q[4 * kk + 1], q[4 * kk + 2], q[4 * kk + 3], desc64(kd + (kk >> 2) * 1024 + (kk & 3) * 2), kk != 0);
  wg_commit();
}
__device__ __forceinline__ void issue_pv(float (&o)[64], const uint32_t (&p)[32], uint32_t vd, int accumulate, bool half) {
  if (half) {
    wg_fence();
#pragma unroll
    for (int kk = 0; kk < 4; kk++)
      wgmma_rs_n128_nmaj(o, p[4 * kk], p[4 * kk + 1], p[4 * kk + 2], p[4 * kk + 3], desc64(vd + kk * 128), kk != 0);
    wg_commit();
  } else {
    wg_fence();
#pragma unroll
    for (int kk = 0; kk < 8; kk++)
      wgmma_rs_n128_nmaj(o, p[4 * kk], p[4 * kk + 1], p[4 * kk + 2], p[4 * kk + 3], desc64(vd + kk * 128), kk ? 1 : accumulate);
    wg_commit();
  }
}
__device__ __forceinline__ void mma16816(float* d, uint32_t a0, uint32_t a1, uint32_t a2, uint32_t a3, uint32_t b0, uint32_t b1) {
  asm volatile("mma.sync.aligned.m16n8k16.row.col.f32.bf16.bf16.f32 {%0, %1, %2, %3}, {%4, %5, %6, %7}, {%8, %9}, {%0, %1, %2, %3};"
               : "+f"(d[0]), "+f"(d[1]), "+f"(d[2]), "+f"(d[3]) : "r"(a0), "r"(a1), "r"(a2), "r"(a3), "r"(b0), "r"(b1));
}
__device__ __forceinline__ uint32_t transp8(uint32_t v) { uint32_t r; asm volatile("movmatrix.sync.aligned.m8n8.trans.b16 %0, %1;" : "=r"(r) : "r"(v)); return r; }
__device__ __forceinline__ float quad_max(float v) { v = fmaxf(v, __shfl_xor_sync(0xffffffffu, v, 1)); return fmaxf(v, __shfl_xor_sync(0xffffffffu, v, 2)); }
constexpr float INV_LO = 5.421011e-20f;
constexpr float INV_HI = 1.0995116e12f;
#define EXB 36
#define SUMA 32
template <bool DIAG, int N> __device__ __forceinline__ constexpr bool hidden(int i) { return DIAG && i >= N - 16 && !(i & 2); }
template <bool DIAG, int I0, int I1, int N> __device__ __forceinline__ void exp_part(float (&s)[N]) {
#pragma unroll
  for (int i = I0; i < I1 && i < N; i++) s[i] = hidden<DIAG, N>(i) ? 0.f : ex2(s[i]);
}
template <bool DIAG, int I0, int I1, int N> __device__ __forceinline__ void sum_part(const float (&s)[N], float& a0, float& a1) {
#pragma unroll
  for (int i = I0; i < I1 && i < N; i++) {
    if (hidden<DIAG, N>(i)) continue;
    if (DIAG && i == 0) a0 = s[i]; else if (DIAG && i == 2) a1 = s[i]; else if (i & 2) a1 += s[i]; else a0 += s[i];
  }
}
template <bool DIAG, int N> __device__ __forceinline__ void pack_p(const float (&s)[N], uint32_t (&p)[32]) {
#pragma unroll
  for (int i = 0; i < N / 2; i++) p[i] = hidden<DIAG, N>(2 * i) ? 0u : pack_bf16(s[2 * i], s[2 * i + 1]);
}
template <int N> __device__ __forceinline__ void mask_diag(float (&s)[N], int lim) {
#pragma unroll
  for (int i = 0; i < 8; i++) {
    constexpr int r = N - 32;
    const bool keep = (i >> 1) * 8 + (i & 1) <= lim;
    const int u = r + (i >> 1) * 4 + (i & 1);
    s[u] = keep ? s[u] : -INFINITY;
    s[u + 18] = keep ? s[u + 18] : -INFINITY;
  }
}
template <bool DIAG, int I1, int N> __device__ __forceinline__ void keep_alive(float (&s)[N], uint32_t zero) {
  if (zero) {
#pragma unroll
    for (int i = 0; i < I1 && i < N; i++) if (!hidden<DIAG, N>(i)) asm volatile("st.volatile.shared.f32 [%0], %1;" :: "r"(zero), "f"(s[i]) : "memory");
    __trap();
  }
}
__device__ __forceinline__ void row_inv(float l0, float l1, float& i0, float& i1) {
  l0 += __shfl_xor_sync(0xffffffffu, l0, 1); l1 += __shfl_xor_sync(0xffffffffu, l1, 1);
  l0 += __shfl_xor_sync(0xffffffffu, l0, 2); l1 += __shfl_xor_sync(0xffffffffu, l1, 2);
  i0 = rcp(l0); i1 = rcp(l1);
}
template <bool B> struct Flag { static constexpr bool v = B; };

__device__ __forceinline__ void attention(const Params& P, const Ctx& X, Cons& C, Cur& c, int cl, uint32_t rank, uint32_t n2, uint32_t wq) {
  float s[64], o[64];
  uint32_t q[32], p[32];
  float l0 = 1.f, l1 = 1.f;
  int acc_o = 0;
  bool half = false;
  const Cur cq = c;
  c.next();
  uint32_t pos = c.s + NSLOT * c.p, nk, nv, xr = 0, kd, kok;
  auto wrap = [](uint32_t v) { return v >= 2 * NSLOT ? v - 2 * NSLOT : v; };
  auto slot_of = [](uint32_t v) { return v >= NSLOT ? v - NSLOT : v; };
  const uint32_t d0 = (X.base & 0x3FFFF) >> 4;
  const int lim = wq * 8 + (X.lane >> 2) - (X.lane & 3) * 2;
#pragma unroll
  for (int i = 0; i < 64; i++) { o[i] = 0.f; s[i] = 0.f; }
#pragma unroll
  for (int i = 0; i < 32; i++) p[i] = 0u;
  const uint32_t stg = X.base + STG_OFF + C.wg * 16384;
  const uint32_t sa = stg + C.frag + ((C.chi ^ C.xr) << 4);
  const __nv_bfloat16* qsrc;
  auto find_q = [&](uint32_t t, bool staged) {
    asm volatile("" : "+r"(t));
    if (staged && q_staged(P, cl, t - 1, n2)) {
      X.wait_stg(C.wg, C.stg_ph ^ 1);
      qsrc = static_cast<const __nv_bfloat16*>(__cvta_shared_to_generic(stg + wq * 1024));
    } else {
      wait_dep(X, t);
      qsrc = g_act + Q_OFF + (((uint32_t)P.p2[cl][t] * 256 + item_row(t, n2, 0, C.wg, rank)) * HD + wq * 512);
      asm volatile("prefetch.global.L1 [%0];" :: "l"(qsrc + (X.lane >> 3) * 2048 + (X.lane & 7) * 64) : "memory");
    }
  };
  auto load_q = [&]() {
#pragma unroll
    for (int kk = 0; kk < 8; kk++) ld4(q[4 * kk], q[4 * kk + 1], q[4 * kk + 2], q[4 * kk + 3], qsrc + X.lane * 8 + (kk >> 1) * 2048 + (kk & 1) * 256);
  };
  auto put_out = [&](const float (&o)[64], float i0, float i1) {
    uint32_t r[32];
#pragma unroll
    for (int i = 0; i < 32; i++) r[i] = pack_bf16(o[2 * i] * ((i & 1) ? i1 : i0), o[2 * i + 1] * ((i & 1) ? i1 : i0));
#pragma unroll
    for (int j = 0; j < 8; j++)
      stsm4((sa ^ ((j & 3) << 5)) + (j >> 2) * 8192, r[4 * j], r[4 * j + 1], r[4 * j + 2], r[4 * j + 3]);
  };
  auto unsafe = [&](float i0, float i1) { return __any_sync(0xffffffffu, !(i0 >= INV_LO) | !(i1 >= INV_LO) | !(i0 <= INV_HI) | !(i1 <= INV_HI)); };
  auto redo = [&](uint32_t t) {
    uint32_t lane = X.lane;
    asm volatile("" : "+r"(t), "+r"(lane));
    const uint32_t it = P.p2[cl][t];
    const int row = item_row(t, n2, it, C.wg, rank);
    const __nv_bfloat16* qa = q_tile(it >> 3, row) + wq * 512 + lane * 8;
#pragma unroll
    for (int i = 0; i < 64; i++) s[i] = 0.f;
    float m0 = -INFINITY, m1 = -INFINITY, r0 = 0.f, r1 = 0.f;
    const uint32_t* kv = reinterpret_cast<const uint32_t*>(g_act + (size_t)(lane >> 2) * ACT_W + (it >> 3) * 128) + (lane & 3);
#pragma unroll 1
    for (int k = -row; k < 64; k += 16, kv += 8 * ACT_W) {
      float z[8];
#pragma unroll
      for (int i = 0; i < 8; i++) z[i] = 0.f;
#pragma unroll 1
      for (int kk = 0; kk < 8; kk++) {
        uint32_t f0, f1, f2, f3;
        ldg4(f0, f1, f2, f3, qa + (kk >> 1) * 2048 + (kk & 1) * 256);
        const uint32_t* kp = kv + ACT_K / 2 + kk * 8;
        mma16816(z, f0, f1, f2, f3, __ldcg(kp), __ldcg(kp + 4));
        mma16816(z + 4, f0, f1, f2, f3, __ldcg(kp + 4 * ACT_W), __ldcg(kp + 4 * ACT_W + 4));
      }
#pragma unroll
      for (int i = 0; i < 8; i++) z[i] = k + (i >> 2) * 8 + (i & 1) - (i & 2) * 16 > lim ? -INFINITY : z[i];
      const float n0 = fmaxf(m0, quad_max(fmaxf(fmaxf(z[0], z[1]), fmaxf(z[4], z[5]))));
      const float n1 = fmaxf(m1, quad_max(fmaxf(fmaxf(z[2], z[3]), fmaxf(z[6], z[7]))));
      const float e0 = ex2(m0 - n0), e1 = ex2(m1 - n1);
      m0 = n0; m1 = n1;
#pragma unroll
      for (int i = 0; i < 8; i++) z[i] = ex2(z[i] - ((i & 2) ? m1 : m0));
      r0 = r0 * e0 + (z[0] + z[1] + z[4] + z[5]); r1 = r1 * e1 + (z[2] + z[3] + z[6] + z[7]);
#pragma unroll
      for (int j = 0; j < 16; j++) {
        s[4 * j] *= e0; s[4 * j + 1] *= e0; s[4 * j + 2] *= e1; s[4 * j + 3] *= e1;
        mma16816(s + 4 * j, pack_bf16(z[0], z[1]), pack_bf16(z[2], z[3]), pack_bf16(z[4], z[5]), pack_bf16(z[6], z[7]),
                 transp8(__ldcg(kv + ACT_V / 2 + j * 4)), transp8(__ldcg(kv + ACT_V / 2 + 4 * ACT_W + j * 4)));
      }
    }
    row_inv(r0, r1, r0, r1);
    put_out(s, r0, r1);
  };
  auto wait_v = [&]() { mbar_wait(X.full(slot_of(nv)), nv >= NSLOT); };
  auto v_desc = [&]() { return d0 + slot_of(nv) * 2048 + 0x4000000; };
  auto softmax = [&](auto diag, auto& s, uint32_t vs, uint32_t e0, uint32_t e1, uint32_t e2) {
    constexpr bool D = decltype(diag)::v;
    nk = wrap(pos + e0);
    xr = (e0 | e2) && X.lane < 2 ? X.rel + slot_of(pos) * 8 : 0;
    nv = wrap(nk + e1);
    nk = e2 ? wrap(nv + 1) : nk;
    pos = wrap(nv + 1 + e2);
    kd = d0 + slot_of(nk) * 2048 + 0x10000;
    if (D) mask_diag(s, lim);
    exp_part<D, 0, EXB>(s);
    sum_part<D, 0, SUMA>(s, l0, l1);
    asm volatile("" : "+f"(l0), "+f"(l1));
    pin(s);
    kok = mbar_test(X.full(slot_of(nk)), nk >= NSLOT);
    if (P.zero) asm volatile("st.volatile.shared.v2.f32 [%0], {%1, %2};" :: "r"(P.zero), "f"(l0), "f"(l1) : "memory");
    keep_alive<D, EXB>(s, P.zero);
    wg_wait<0>();
    pin(o);
    pin(s);
    LF(2);
    if (vs < NSLOT) X.release(vs);
    exp_part<D, EXB, 64>(s);
    sum_part<D, SUMA, 64>(s, l0, l1);
    pack_p<D>(s, p);
    LF(15);
    if (!D && !kok) mbar_wait(X.full(slot_of(nk)), nk >= NSLOT);
  };
  if (C.wg && X.lane < 2) xr = X.rel + c.s * 8;
  nv = nk = wrap(pos + C.wg);
  pos = wrap(nk + 1);
  kd = d0 + slot_of(nk) * 2048 + 0x10000;
  LF(15);
  X.wait_full(cq);
  LF(5);
#pragma unroll
  for (int kk = 0; kk < 8; kk++)
    lds4(q[4 * kk], q[4 * kk + 1], q[4 * kk + 2], q[4 * kk + 3], X.slot(cq.s) + C.wg * 16384 + wq * 1024 + X.lane * 16 + (kk >> 1) * 4096 + (kk & 1) * 512);
  X.release_dep(cq.s, (q[0] ^ q[4] ^ q[8] ^ q[12] ^ q[16] ^ q[20] ^ q[24] ^ q[28]) & P.zero);
  mbar_wait(X.full(slot_of(nk)), nk >= NSLOT);
  bool more, skip;
  uint32_t hnext = half_first(0, n2, C.wg, rank);
  for (uint32_t t = 0;; t++) {
    const bool hnew = hnext;
    bool bad;
    int nblk;
    float i0, i1;
    uint32_t sok;
    auto first_block = [&](auto& s) {
      X.order_wait(C.wg);
      LG(1);
      LF(1);
      issue_qk(s, q, kd);
      LF(3);
      uint32_t tt = t;
      asm volatile("" : "+r"(tt));
      skip = (tt ^ C.wg) & 1;
      nblk = 2 * (P.p2[cl][tt] & 7) + 2 - (skip ? 1 : 0);
      more = tt + 1 < n2;
      hnext = half_first(tt + 1, n2, C.wg, rank);
      asm volatile("" : "+r"(hnext));
      const uint32_t ks = slot_of(nk), vs = slot_of(nv);
      auto chores = [&]() {
        if (xr) mbar_arrive_cluster(xr);
        if (nblk == 1 && more) find_q(t + 1, false);
      };
      if (sizeof(s) == 256) {
        chores();
        row_inv(l0, l1, i0, i1);
        bad = unsafe(i0, i1);
      }
      LF(5);
      wait_v();
      LF(9);
      if (t > 0) issue_pv(o, p, v_desc(), acc_o, half); else wg_commit();
      order_pass(C.wg);
      if (sizeof(s) != 256) chores();
      LF(6);
      wg_wait<1>();
      pin(s);
      LF(7);
      X.release(ks);
      if (nblk == 1 && more) load_q();
      if (sizeof(s) != 256) { row_inv(l0, l1, i0, i1); bad = unsafe(i0, i1); }
      sok = mbar_test(X.stg_empty(C.wg), C.stg_ph ^ 1);
      softmax(Flag<true>(), s, t > 0 ? vs : NSLOT, skip, nblk > 1 || more, 0);
    };
    if (hnew) {
      float sh[32];
#pragma unroll
      for (int i = 0; i < 32; i++) sh[i] = 0.f;
      first_block(sh);
#pragma unroll
      for (int i = 0; i < 64; i++) s[i] = i < 32 ? sh[i] : 0.f;
    } else {
      first_block(s);
    }
    LF(8);
    half = hnew;
    acc_o = 0;
    if (t > 0) {
      if (!sok) X.wait_stg(C.wg, C.stg_ph ^ 1);
      LF(11);
      if (__builtin_expect(bad, 0)) redo(t - 1); else put_out(o, i0, i1);
      stg_publish(X, C);
    }
    LF(14);
    if (!kok) mbar_wait(X.full(slot_of(nk)), nk >= NSLOT);
    LF(10);
    for (int b = nblk - 1; b > 0; b--) {
      X.order_wait(C.wg);
      LG(0);
      LF(0);
      issue_qk(s, q, kd);
      const uint32_t ks = slot_of(nk), vs = slot_of(nv);
      if (xr) mbar_arrive_cluster(xr);
      if (b == 1 && more) find_q(t + 1, true);
      wait_v();
      issue_pv(o, p, v_desc(), acc_o, half);
      order_pass(C.wg);
      LF(12);
      half = false;
      acc_o = 1;
      wg_wait<1>();
      pin(s);
      LF(13);
      X.release(ks);
      if (b == 1 && more) load_q();
      softmax(Flag<false>(), s, vs, 0, b > 1 || more, b == 1 && more && !skip);
      LF(4);
    }
    if (!more) break;
  }
  if (skip && !acc_o) { X.order_wait(C.wg); if (xr) mbar_arrive_cluster(xr); }
  wait_v();
  LG(1);
  issue_pv(o, p, v_desc(), acc_o, half);
  float i0, i1;
  row_inv(l0, l1, i0, i1);
  const bool bad = unsafe(i0, i1);
  X.wait_stg(C.wg, C.stg_ph ^ 1);
  wg_wait<0>();
  pin(o);
  X.release(slot_of(nv));
  c.s = slot_of(pos);
  if (__builtin_expect(bad, 0)) redo(n2 - 1); else put_out(o, i0, i1);
  stg_publish(X, C);
}

__device__ __forceinline__ void gemm2_loop(const Params& P, const Ctx& X, Cons& C, uint32_t& st, float (&acc)[128], uint32_t (&x)[64], int s0, int s1, int nsteps, int lag) {
  uint32_t prev = 0;
  auto get_x = [&](int h) {
    X.wait_stg(C.wg, C.stg_ph ^ 1);
    uint32_t dep = 0;
#pragma unroll
    for (int j = 0; j < 8; j++) {
      ldsm4(x[h + 4 * j], x[h + 4 * j + 1], x[h + 4 * j + 2], x[h + 4 * j + 3],
            X.base + STG_OFF + C.wg * 16384 + (j >> 2) * 8192 + C.frag + (((j & 3) * 2 + C.chi) ^ C.xr) * 16);
      dep ^= x[h + 4 * j];
    }
    if (X.lane == 0) mbar_arrive(X.stg_full(C.wg) + (dep & P.zero));
    C.stg_ph ^= 1;
  };
  for (int s = s0; s < s1; s++) {
    const bool hold = C.wg && s == nsteps - lag;
    if (hold) { wg_wait<0>(); X.release2(prev); bar_sync<5>(256); }
    mbar_wait(X.full2(st), (s >> 2) & 1);
    const uint64_t da = mkdesc(X.stage(st) + C.wg * 8192, 16, 1024);
    const uint64_t db = mkdesc(X.stage(st) + 16384, 8192, 1024);
    wg_fence();
#pragma unroll
    for (int kk = 0; kk < 4; kk++) wgmma_ss_n256_nmaj(acc, da + kk * 2, db + kk * 128, kk ? 1 : s);
    wg_commit();
    if (!C.wg && s == nsteps - 1) bar_arrive<5>(256);
    if (s == 32) get_x(0);
    if (s == 36) get_x(32);
    wg_wait<1>();
    if (s > s0 && !hold && s <= nsteps - 3) X.release2(prev);
    prev = st;
    st = (st + 1) & 3;
  }
  if (s1 < nsteps) { wg_wait<0>(); X.release2(prev); }
  else cluster_arrive();
}

#define TL(i)
#define AHEAD 4
__device__ __forceinline__ void gemm2(const Params& P, const Ctx& X, Cons& C, Cur& c, uint32_t role, uint32_t rank) {
  uint32_t st = first_stage(c.s);
  C.frag = ((threadIdx.x & 96) / 2 + (X.lane & 15)) * 128;
  const bool dn = role & ROLE_D;
  const uint32_t gidx = (role & 15) * 4 + rank * 2 + C.wg;
  float acc[128];
#pragma unroll
  for (int i = 0; i < 128; i++) acc[i] = 0.f;
  const uint32_t p0 = dn ? C.wg : 1;
#pragma unroll 1
  for (uint32_t pass = p0; pass < 2; pass++) {
    uint32_t x[64];
#pragma unroll
    for (int i = 0; i < 64; i++) x[i] = 0u;
    LG(7);
    const int nsteps = dn ? 28 : 2 * NH;
    gemm2_loop(P, X, C, st, acc, x, pass > p0 ? AHEAD : 0, pass ? nsteps : AHEAD, nsteps, dn ? LAGD : LAGO);
    if (dn) {
      wg_wait<0>();
      pin(acc);
      LG(3);
      __nv_bfloat16* gp = g_act + G_OFF + gidx * 16384 + (threadIdx.x & 96) * 32 + X.lane * 8;
#pragma unroll 1
      for (int q = pass ? 0 : 1; q < 2; q++) {
        float y[64];
#pragma unroll
        for (int k = 0; k < 6; k++) {
          if (k < 4) {
#pragma unroll
            for (int i = 16 * k; i < 16 * k + 16; i++) y[i] = ex2(-1.4426950408889634f * acc[i]);
          }
          if (k >= 1 && k < 5) {
#pragma unroll
            for (int i = 16 * k - 16; i < 16 * k; i++) y[i] = rcp(1.0f + y[i]);
          }
          if (k >= 2) {
#pragma unroll
            for (int j = 2 * k - 4; j < 2 * k - 2; j++) {
              stg4_if(pass, gp + (j >> 2) * 4096 + (j & 3) * 256, pack_bf16(acc[8 * j] * y[8 * j], acc[8 * j + 1] * y[8 * j + 1]), pack_bf16(acc[8 * j + 2] * y[8 * j + 2], acc[8 * j + 3] * y[8 * j + 3]),
                      pack_bf16(acc[8 * j + 4] * y[8 * j + 4], acc[8 * j + 5] * y[8 * j + 5]), pack_bf16(acc[8 * j + 6] * y[8 * j + 6], acc[8 * j + 7] * y[8 * j + 7]));
#pragma unroll
              for (int i = 8 * j; i < 8 * j + 8; i++) acc[i] = pass ? acc[i + 64] : acc[i];
            }
          }
        }
        gp += 8192;
      }
      LG(5);
      __syncwarp();
      if (X.lane == 0 && pass) red_release(&g_flags[FL_G + gidx]);
      LG(6);
    } else {
      const uint32_t sa = X.base + STG_OFF + C.wg * 16384, sb = X.stage(st) + C.wg * 16384;
      const uint32_t sg[4] = {sa, sa + 8192, sb, sb + 8192};
      uint32_t g[4][16];
      auto fetch = [&](int q) {
#pragma unroll
        for (int j = 0; j < 4; j++) lds4(g[q][4 * j], g[q][4 * j + 1], g[q][4 * j + 2], g[q][4 * j + 3], sg[q] + (threadIdx.x & 96) * 64 + j * 512 + X.lane * 16);
      };
      auto finish = [&](int q) {
#pragma unroll
        for (int e = 0; e < 16; e++) g[q][e] = add_bf16x2(x[16 * q + e], mul_bf16x2(pack_bf16(acc[32 * q + 2 * e], acc[32 * q + 2 * e + 1]), g[q][e]));
#pragma unroll
        for (int j = 0; j < 4; j++)
          stsm4(sg[q] + C.frag + ((j * 2 + C.chi) ^ C.xr) * 16, g[q][4 * j], g[q][4 * j + 1], g[q][4 * j + 2], g[q][4 * j + 3]);
        __syncwarp();
        if (X.lane == 0) mbar_arrive(X.out_full(C.wg, q));
      };
      X.wait_stg(C.wg, C.stg_ph ^ 1);
      fetch(0);
      wg_wait<0>();
      pin(acc);
      fetch(1);
      finish(0);
      mbar_wait(X.g_full(C.wg), 0);
      fetch(2);
      finish(1);
      fetch(3);
      finish(2);
      finish(3);
    }
    __syncwarp();
  }
}

__global__ void __cluster_dims__(2, 1, 1) __launch_bounds__(384, 1) fused_kernel(const __grid_constant__ Params P) {
  extern __shared__ uint8_t smem_raw[];
  Ctx X;
  X.base = (smem_u32(smem_raw) + 1023) & ~1023u;
  X.lane = threadIdx.x & 31;
  const uint32_t rank = cluster_rank();
  const int cl = blockIdx.x >> 1;
  const uint32_t warp = __shfl_sync(0xffffffffu, threadIdx.x >> 5, 0);
  TS(0);
  if (threadIdx.x == 256) LX(0);
  if (warp == 9 && X.lane < 14) asm volatile("prefetch.tensormap [%0];" :: "l"(&P.act128 + X.lane) : "memory");
  const uint32_t op0 = P.first[cl][0];
  const bool x0 = op0 & 8;
  int wcol;
  const CUtensorMap* wm = slice_src(P, P.first[cl][1], rank, wcol);
  auto first_a = [&](int k) {
    const uint32_t sl = x0 ? k : 2 * k;
    mbar_expect_tx(X.full(sl), SLOT);
    tma_load(X.slot(sl), x0 ? &P.x128 : &P.ckv128, k * 128, (op0 & 7) * 256 + rank * 128, X.full(sl));
    tma_load(X.slot(sl) + 16384, x0 ? &P.x128 : &P.ckv128, k * 128 + 64, (op0 & 7) * 256 + rank * 128, X.full(sl));
  };
  if (threadIdx.x == 256) {
    for (int i = 0; i < NSLOT; i++) mbar_init(X.full(i), 1);
    fence_async_smem();
    LX(1);
    if (op0 != 0xFF) {
#pragma unroll 1
      for (int k = 0; k < PRE_C; k++) first_a(k);
    }
    LX(2);
    asm volatile("fence.mbarrier_init.release.cluster;" ::: "memory");
  }
  if (threadIdx.x == 352) {
    for (int i = 0; i < NSLOT; i++) mbar_init(X.empty(i), 16);
    for (int i = 0; i < 2; i++) { mbar_init(X.stg_full(i), 4); mbar_init(X.stg_empty(i), 1); mbar_init(X.g_full(i), 1); }
    for (int i = 0; i < 4; i++) { mbar_init(X.full2(i), 1); mbar_init(X.empty2(i), 16); }
    mbar_init(X.done_bar(), 11);
    for (int i = 0; i < 8; i++) mbar_init(X.out_full(0, i), 4);
    asm volatile("st.shared.v2.u32 [%0], {%1, %1};" :: "r"(X.dep_cnt()), "r"(0) : "memory");
    asm volatile("st.shared.v2.u32 [%0], {%1, %1};" :: "r"(X.g2_pos()), "r"(0) : "memory");
    asm volatile("fence.mbarrier_init.release.cluster;" ::: "memory");
    fence_async_smem();
  }
  __syncthreads();
  cluster_arrive();
  if (warp < 8) {
    asm volatile("setmaxnreg.inc.sync.aligned.u32 240;");
    X.lane = __shfl_sync(0xffffffffu, X.lane, X.lane);
    X.rel = mapa(X.base + BAR_OFF + 64, X.lane & 1);
    Cons C;
    C.wg = warp >> 2;
    {
      const uint32_t r = (warp & 3) * 8 + (X.lane & 7) + ((X.lane >> 3) & 1) * 32;
      C.frag = r * 128;
      C.xr = r & 7;
      C.chi = X.lane >> 4;
    }
    C.stg_ph = 0;
    LP(2);
    Cur c{0, 0};
    if (C.wg == 1) bar_arrive<1>(256);
    cluster_wait();
    if (threadIdx.x == 0) TS(1);
    phase1(P, X, C, c, cl);
    TS(2 + C.wg);
    X.dump(0);
    const uint32_t n2 = P.n2[cl], role = P.role[cl];
    if (n2) attention(P, X, C, c, cl, rank, n2, warp & 3);
    TS(4 + C.wg);
    if (role) gemm2(P, X, C, c, role, rank); else cluster_arrive();
    TS(8 + C.wg);
    X.dump(3);
    if (X.lane == 0) mbar_arrive(X.done_bar());
  } else {
    asm volatile("setmaxnreg.dec.sync.aligned.u32 24;");
    if (warp > 8) {
      cluster_wait();
      cluster_arrive();
      if (warp > 10) {
        if (X.lane == 0) dep_warp(P, X, cl, rank);
      } else {
        storer(P, X, cl, rank, warp - 9);
        if (X.lane == 0) mbar_arrive(X.done_bar());
      }
    } else {
      if (X.lane == 0 && x0 && op0 != 0xFF) {
#pragma unroll 1
        for (int k = PRE_C; k < 4; k++) first_a(k);
      }
      __syncwarp();
      cluster_wait();
      cluster_arrive();
      LX(6);
      if (X.lane == 0 && op0 != 0xFF) {
#pragma unroll 1
        for (int k = 0; k < (x0 ? 2 : 3); k++) {
          if (!x0 && k >= PRE_C) first_a(k);
          const uint32_t sl = x0 ? 4 + k : 2 * k + 1;
          mbar_expect_tx(X.full(sl), SLOT);
          tma_load_mc(X.slot(sl) + rank * 16384, wm, wcol, k * 128, X.full(sl));
        }
      }
      LX(7);
      __syncwarp();
      producer(P, X, cl, rank);
      if (X.lane == 0) mbar_arrive(X.done_bar());
    }
  }
  __syncwarp();
  cluster_wait();
}

typedef CUresult (*EncodeFn)(CUtensorMap*, CUtensorMapDataType, cuuint32_t, void*, const cuuint64_t*, const cuuint64_t*,
                             const cuuint32_t*, const cuuint32_t*, CUtensorMapInterleave, CUtensorMapSwizzle,
                             CUtensorMapL2promotion, CUtensorMapFloatOOBfill);

void make_map(EncodeFn enc, CUtensorMap* m, const void* ptr, uint64_t rows, uint64_t cols, uint32_t box_rows) {
  cuuint64_t dims[2] = {cols, rows};
  cuuint64_t strides[1] = {cols * 2};
  cuuint32_t box[2] = {64, box_rows};
  cuuint32_t es[2] = {1, 1};
  CUresult r = enc(m, CU_TENSOR_MAP_DATA_TYPE_BFLOAT16, 2, const_cast<void*>(ptr), dims, strides, box, es,
                   CU_TENSOR_MAP_INTERLEAVE_NONE, CU_TENSOR_MAP_SWIZZLE_128B, CU_TENSOR_MAP_L2_PROMOTION_L2_128B,
                   CU_TENSOR_MAP_FLOAT_OOB_FILL_NONE);
  if (r != CUDA_SUCCESS) fprintf(stderr, "tensor map encode failed: %d\n", (int)r);
}

const unsigned char TAB_P1[8][40] = {
  {128,0,3,6,9,12,14,15,16,17,18,19,20,21,22,23,24,25,26,27,28,29,30,31,255},
  {128,32,35,38,41,44,46,47,48,49,50,51,52,53,54,55,56,57,58,59,60,61,62,63,255},
  {136,64,66,68,96,70,98,72,74,100,76,102,78,104,80,82,106,84,108,86,110,88,90,112,92,114,94,116,118,120,122,255},
  {136,65,67,69,97,71,99,73,75,101,77,103,79,105,81,83,107,85,109,87,111,89,91,113,93,115,95,117,119,121,123,255},
  {128,1,4,7,10,13,255},
  {128,33,36,39,42,45,255},
  {128,2,5,8,11,255},
  {128,34,37,40,43,255},
};
const unsigned char TAB_ROLE[66] = {32,34,36,38,40,42,44,46,33,35,37,39,41,43,45,47,16,18,20,22,24,26,28,30,17,19,21,23,25,27,29,31,0,0,0,0,0,0,0,0,0,0,0,0,0,0,0,0,0,0,0,0,0,0,0,0,0,0,0,0,0,0,0,0,0,0,};
const unsigned char TAB_N2[66] = {0,0,0,0,0,0,0,0,0,0,0,0,0,0,0,0,0,0,0,0,0,0,0,0,0,0,0,0,0,0,0,0,6,6,8,8,8,9,7,7,6,8,8,11,6,8,8,10,6,5,7,6,6,8,6,9,6,7,6,10,9,9,11,6,7,8,};
const unsigned char TAB_P2[66][16] = {
  {0},
  {0},
  {0},
  {0},
  {0},
  {0},
  {0},
  {0},
  {0},
  {0},
  {0},
  {0},
  {0},
  {0},
  {0},
  {0},
  {0},
  {0},
  {0},
  {0},
  {0},
  {0},
  {0},
  {0},
  {0},
  {0},
  {0},
  {0},
  {0},
  {0},
  {0},
  {0},
  {30,75,124,154,156,223,0},
  {37,86,141,152,172,230,0},
  {32,33,52,95,158,204,210,224,0},
  {25,35,58,65,106,133,174,229,0},
  {36,68,73,101,137,164,176,221,0},
  {24,42,53,98,112,123,129,189,247,0},
  {39,82,81,143,188,211,234,0},
  {19,61,93,131,205,185,245,0},
  {29,78,126,163,195,253,0},
  {28,71,125,155,215,232,240,248,0},
  {16,47,100,142,161,196,193,226,0},
  {18,55,96,122,132,145,179,192,202,208,251,0},
  {31,92,135,190,218,250,0},
  {23,72,103,147,180,212,216,249,0},
  {17,40,46,110,121,167,219,242,0},
  {20,49,64,94,120,150,160,168,203,244,0},
  {21,70,115,162,191,228,0},
  {22,77,109,181,231,0},
  {14,56,84,104,117,183,254,0},
  {11,45,91,127,207,252,0},
  {13,79,130,173,198,235,0},
  {9,38,57,108,149,178,186,246,0},
  {6,66,90,118,175,220,0},
  {12,48,59,102,146,136,170,206,243,0},
  {5,60,111,148,169,239,0},
  {1,34,62,119,144,197,255,0},
  {15,87,113,166,214,233,0},
  {3,50,67,80,88,114,105,151,177,238,0},
  {8,26,54,85,165,187,194,209,225,0},
  {0,27,51,74,116,128,139,199,227,0},
  {10,41,43,83,89,134,153,213,201,217,241,0},
  {4,63,97,138,159,222,0},
  {2,44,76,99,157,182,236,0},
  {7,69,107,140,171,184,200,237,0},
};
const unsigned char TAB_OH[8][32] = {
  {0,1,2,3,4,5,6,7,8,9,10,11,12,13,14,15,16,17,18,19,20,21,22,23,24,25,26,28,27,29,30,31,},
  {0,1,2,3,4,5,6,7,8,9,10,11,12,13,14,15,16,17,18,19,20,21,22,23,24,25,26,27,28,29,30,31,},
  {0,1,3,2,4,5,6,7,8,9,10,11,12,13,14,15,16,17,18,19,20,21,22,23,24,25,26,27,28,29,30,31,},
  {0,1,3,2,4,5,6,7,8,9,10,11,12,13,14,15,16,17,18,19,20,21,22,23,24,25,26,27,28,29,30,31,},
  {0,1,2,3,4,5,6,7,8,9,10,11,12,13,14,15,16,17,18,19,20,21,22,23,24,25,26,27,28,29,30,31,},
  {0,1,2,3,4,5,6,7,8,9,10,11,12,13,14,15,16,17,18,19,20,21,22,23,24,25,26,27,28,29,30,31,},
  {0,1,2,3,4,5,6,7,8,9,10,11,12,13,14,15,16,17,18,19,20,21,22,23,24,25,26,27,28,29,30,31,},
  {0,1,2,3,4,5,6,7,8,9,10,11,12,13,14,15,16,17,18,19,20,21,22,23,24,25,26,27,28,29,30,31,},
};
const unsigned short TAB_LAST[66][16] = {
  {0,0,0,0,0,0,0,0,0,0,0,0,0,0,0,0},
  {0,0,0,0,0,0,0,0,0,0,0,0,0,0,0,0},
  {0,0,0,0,0,0,0,0,0,0,0,0,0,0,0,0},
  {0,0,0,0,0,0,0,0,0,0,0,0,0,0,0,0},
  {0,0,0,0,0,0,0,0,0,0,0,0,0,0,0,0},
  {0,0,0,0,0,0,0,0,0,0,0,0,0,0,0,0},
  {0,0,0,0,0,0,0,0,0,0,0,0,0,0,0,0},
  {0,0,0,0,0,0,0,0,0,0,0,0,0,0,0,0},
  {0,0,0,0,0,0,0,0,0,0,0,0,0,0,0,0},
  {0,0,0,0,0,0,0,0,0,0,0,0,0,0,0,0},
  {0,0,0,0,0,0,0,0,0,0,0,0,0,0,0,0},
  {0,0,0,0,0,0,0,0,0,0,0,0,0,0,0,0},
  {0,0,0,0,0,0,0,0,0,0,0,0,0,0,0,0},
  {0,0,0,0,0,0,0,0,0,0,0,0,0,0,0,0},
  {0,0,0,0,0,0,0,0,0,0,0,0,0,0,0,0},
  {0,0,0,0,0,0,0,0,0,0,0,0,0,0,0,0},
  {0,0,0,0,0,0,0,0,0,0,0,0,0,0,0,0},
  {0,0,0,0,0,0,0,0,0,0,0,0,0,0,0,0},
  {0,0,0,0,0,0,0,0,0,0,0,0,0,0,0,0},
  {0,0,0,0,0,0,0,0,0,0,0,0,0,0,0,0},
  {0,0,0,0,0,0,0,0,0,0,0,0,0,0,0,0},
  {0,0,0,0,0,0,0,0,0,0,0,0,0,0,0,0},
  {0,0,0,0,0,0,0,0,0,0,0,0,0,0,0,0},
  {0,0,0,0,0,0,0,0,0,0,0,0,0,0,0,0},
  {0,0,0,0,0,0,0,0,0,0,0,0,0,0,0,0},
  {0,0,0,0,0,0,0,0,0,0,0,0,0,0,0,0},
  {0,0,0,0,0,0,0,0,0,0,0,0,0,0,0,0},
  {0,0,0,0,0,0,0,0,0,0,0,0,0,0,0,0},
  {0,0,0,0,0,0,0,0,0,0,0,0,0,0,0,0},
  {0,0,0,0,0,0,0,0,0,0,0,0,0,0,0,0},
  {0,0,0,0,0,0,0,0,0,0,0,0,0,0,0,0},
  {0,0,0,0,0,0,0,0,0,0,0,0,0,0,0,0},
  {0,0,0,0,0,65535,0,0,0,0,0,0,0,0,0,0},
  {0,0,0,0,0,16383,0,0,0,0,0,0,0,0,0,0},
  {0,0,0,65535,0,0,63,3,0,0,0,0,0,0,0,0},
  {0,0,0,0,0,0,16383,4095,0,0,0,0,0,0,0,0},
  {0,0,0,4095,0,0,0,4095,0,0,0,0,0,0,0,0},
  {0,0,0,0,0,0,0,0,65535,0,0,0,0,0,0,0},
  {65535,0,0,65535,0,0,63,0,0,0,0,0,0,0,0,0},
  {0,0,4095,0,0,15,4095,0,0,0,0,0,0,0,0,0},
  {0,16383,16383,0,0,4095,0,0,0,0,0,0,0,0,0,0},
  {0,65535,0,0,65535,0,0,3,0,0,0,0,0,0,0,0},
  {0,65535,0,16383,0,0,15,63,0,0,0,0,0,0,0,0},
  {0,65535,0,0,0,0,0,0,63,0,255,0,0,0,0,0},
  {65535,0,65535,16383,63,63,0,0,0,0,0,0,0,0,0,0},
  {65535,0,61440,0,0,1023,3,15,0,0,0,0,0,0,0,0},
  {0,0,16383,0,0,65535,0,63,0,0,0,0,0,0,0,0},
  {0,0,0,0,0,0,0,0,0,1023,0,0,0,0,0,0},
  {0,16383,0,0,49152,1023,0,0,0,0,0,0,0,0,0,0},
  {0,4095,4095,0,65535,0,0,0,0,0,0,0,0,0,0,0},
  {0,0,0,0,4095,49152,16383,0,0,0,0,0,0,0,0,0},
  {0,0,0,65535,65520,1023,0,0,0,0,0,0,0,0,0,0},
  {0,65535,0,0,16383,255,0,0,0,0,0,0,0,0,0,0},
  {0,16383,0,0,0,0,0,16383,0,0,0,0,0,0,0,0},
  {16383,0,0,16383,65535,1023,0,0,0,0,0,0,0,0,0,0},
  {0,0,0,0,0,0,0,16383,255,0,0,0,0,0,0,0},
  {0,0,65535,0,0,65535,0,0,0,0,0,0,0,0,0,0},
  {0,0,0,65535,0,0,65535,0,0,0,0,0,0,0,0,0},
  {65535,65535,0,0,16383,15,0,0,0,0,0,0,0,0,0,0},
  {0,0,0,0,0,0,0,65535,0,16383,0,0,0,0,0,0},
  {0,0,0,4095,0,0,48,15,15,0,0,0,0,0,0,0},
  {0,0,0,0,0,0,0,65520,255,0,0,0,0,0,0,0},
  {0,0,0,0,0,0,0,0,15,15,15,0,0,0,0,0},
  {0,65535,0,0,65535,16383,0,0,0,0,0,0,0,0,0,0},
  {0,0,0,0,0,16383,1023,0,0,0,0,0,0,0,0,0},
  {65535,4095,0,1023,0,0,0,4095,0,0,0,0,0,0,0,0},
};

void build_schedule(Params& P, int nc) {
  memset(P.p1, 0xFF, sizeof(P.p1));
  memset(P.p2, 0, sizeof(P.p2));
  memset(P.last, 0, sizeof(P.last));
  memset(P.n2, 0, sizeof(P.n2));
  memset(P.role, 0, sizeof(P.role));
  P.nctas = 2 * nc;
  P.zero = 0;
  if (nc == MAXC) {
    for (int c = 0; c < 64; c++) {
      for (int i = 0; TAB_P1[c >> 3][i] != 255; i++) P.p1[c][i] = TAB_P1[c >> 3][i] | ((TAB_P1[c >> 3][i] & 0x80) ? (c & 7) : 0);
    }
    for (int k = 0; k < 2; k++) {
      P.p1[64 + k][0] = P.p1[20 * k][0];
      for (int g = 0; g < 2; g++) {
        uint8_t* e = P.p1[20 * k + 8 * g];
        while (e[1] != 0xFF) e++;
        P.p1[64 + k][1 + g] = *e;
        *e = 0xFF;
      }
    }
    for (int c = 0; c < MAXC; c++) { P.role[c] = TAB_ROLE[c]; P.n2[c] = TAB_N2[c]; memcpy(P.p2[c], TAB_P2[c], 16); memcpy(P.last[c], TAB_LAST[c], 32); }
    memcpy(P.oh, TAB_OH, sizeof(P.oh));
    return;
  }
  const int per = (992 + nc - 1) / nc;
  int c = 0, len = 0, cnt = 0;
  for (int col = 0; col < 16; col++) {
    bool fresh = true;
    for (int k = 0; k < ((col & 8) ? 60 : 64); k++) {
      if (cnt == per) { c++; len = 0; cnt = 0; fresh = true; }
      if (fresh) { P.p1[c][len++] = (uint8_t)(0x80 | col); fresh = false; }
      P.p1[c][len++] = (uint8_t)((col & 8) ? 64 + k : k);
      cnt++;
    }
  }
  float av[MAXC];
  for (int i = 0; i < nc; i++) { av[i] = i < 16 ? 32.f : (i < 32 ? 15.f : 0.f); P.role[i] = (uint8_t)(i < 16 ? ROLE_O | i : (i < 32 ? ROLE_D | (i - 16) : 0)); }
  for (int i = 0; i < 256; i++) {
    const int it = (i & ~7) | (7 - (i & 7));
    int best = -1;
    for (int k = 0; k < nc; k++) if (P.n2[k] < P2LEN && (best < 0 || av[k] < av[best])) best = k;
    P.p2[best][P.n2[best]++] = (uint8_t)it;
    av[best] += 2 * (it & 7) + 2.5f;
  }
  for (int j = 0; j < 8; j++) for (int h = 0; h < NH; h++) P.oh[j][h] = (uint8_t)h;
}

}

extern "C" void kernel_launch(void* const* d_in, const int* in_sizes, int n_in, void* d_out, int out_size) {
  static Params P;
  static int nc = 0;
  static const void* cached[11];
  bool same = nc > 0 && cached[10] == d_out;
  for (int i = 0; i < 10 && same; i++) same = cached[i] == d_in[i];
  if (!same) {
    void* fn = nullptr;
    cudaDriverEntryPointQueryResult qr;
    cudaGetDriverEntryPoint("cuTensorMapEncodeTiled", &fn, cudaEnableDefault, &qr);
    EncodeFn enc = (EncodeFn)fn;
    void* act = nullptr;
    cudaGetSymbolAddress(&act, g_act);
    make_map(enc, &P.act128, act, S_LEN, ACT_W, 128);
    make_map(enc, &P.act64, act, S_LEN, ACT_W, 64);
    make_map(enc, &P.x128, d_in[0], S_LEN, DM, 128);
    make_map(enc, &P.ckv128, d_in[1], S_LEN, DM, 128);
    make_map(enc, &P.wq, d_in[2], DM, NH * HD, 128);
    make_map(enc, &P.wuk, d_in[3], DM, NH * HD, 128);
    make_map(enc, &P.wuv, d_in[4], DM, NH * HD, 128);
    make_map(enc, &P.wo, d_in[5], NH * HD, DM, 64);
    make_map(enc, &P.wg, d_in[7], DM, DFF, 128);
    make_map(enc, &P.wu, d_in[8], DM, DFF, 128);
    make_map(enc, &P.wd, d_in[9], DFF, DM, 64);
    make_map(enc, &P.x64, d_in[0], S_LEN, DM, 64);
    make_map(enc, &P.out64, d_out, S_LEN, DM, 64);
    {
      cuuint64_t dims[3] = {64, 128, NH * S_LEN / 64}, strides[2] = {128, 16384};
      cuuint32_t box[3] = {64, 64, 2}, es[3] = {1, 1, 1};
      enc(&P.ctx3, CU_TENSOR_MAP_DATA_TYPE_BFLOAT16, 3, static_cast<__nv_bfloat16*>(act) + Q_OFF, dims, strides, box, es, CU_TENSOR_MAP_INTERLEAVE_NONE,
          CU_TENSOR_MAP_SWIZZLE_NONE, CU_TENSOR_MAP_L2_PROMOTION_L2_128B, CU_TENSOR_MAP_FLOAT_OOB_FILL_NONE);
    }
    cudaFuncSetAttribute(fused_kernel, cudaFuncAttributeMaxDynamicSharedMemorySize, SMEM_BYTES);
    if (nc == 0) {
      cudaLaunchConfig_t cfg = {};
      cfg.gridDim = dim3(2 * MAXC); cfg.blockDim = dim3(384); cfg.dynamicSmemBytes = SMEM_BYTES;
      cudaLaunchAttribute at[1];
      at[0].id = cudaLaunchAttributeClusterDimension;
      at[0].val.clusterDim.x = 2; at[0].val.clusterDim.y = 1; at[0].val.clusterDim.z = 1;
      cfg.attrs = at; cfg.numAttrs = 1;
      int n = 0;
      if (cudaOccupancyMaxActiveClusters(&n, fused_kernel, &cfg) != cudaSuccess || n <= 0) { n = MAXC; (void)cudaGetLastError(); }
      nc = n < MAXC ? n : MAXC;
      build_schedule(P, nc);
      for (int c = 0; c < MAXC; c++) memcpy(P.first[c], P.p1[c], 2);
    }
    for (int i = 0; i < 10; i++) cached[i] = d_in[i];
    cached[10] = d_out;
  }
  fused_kernel<<<2 * nc, 384, SMEM_BYTES>>>(P);
}
```
